```python
import torch

def _softmax(x, axis=-1):
    return torch.softmax(x, dim=axis)
def _gelu(x):
    return torch.nn.functional.gelu(x, approximate="tanh")
def _silu(x):
    return torch.nn.functional.silu(x)
def _sigmoid(x):
    return torch.sigmoid(x)
def _layernorm(x, axis=-1, eps=1e-5):
    m = x.mean(dim=axis, keepdim=True)
    v = x.var(dim=axis, keepdim=True, unbiased=False)
    return (x - m) / torch.sqrt(v + eps)
def _scatter_add(tgt, idx, src, axis=0):
    return tgt.clone().index_add_(axis, idx, src)
def _segment_sum(src, seg, n):
    out = torch.zeros((n,) + src.shape[1:], dtype=src.dtype)
    return out.index_add_(0, seg, src)
def _pad(x, pw):
    flat = tuple(v for pair in reversed(pw) for v in pair)
    return torch.nn.functional.pad(x, flat)

kernel_name = 'recurrent_scan__gqa_block_cached__geglu_ffn__decode'

def setup_inputs():

    _w = (lambda a: (lambda t: t.to(torch.bfloat16) if t.is_floating_point() else t)(torch.as_tensor(a)))
    def _A_setup():
        B, Sq, D = 8, 1, 576
        Hq, Hkv, Sk, Dh = 32, 16, 8192, 128
        assert Hq % Hkv == 0, (Hq, Hkv)
        return {
            "x": _w((lambda *s: torch.randn(*s, dtype=torch.bfloat16) * 0.05)(B, Sq, D)),
            "k_cache": _w((lambda *s: torch.randn(*s, dtype=torch.bfloat16) * 0.8)(B, Hkv, Sk, Dh)),
            "v_cache": _w((lambda *s: torch.randn(*s, dtype=torch.bfloat16) * 0.2)(B, Hkv, Sk, Dh)),
            "wq": _w((lambda *s: torch.randn(*s, dtype=torch.bfloat16) * 0.8)(D, Hq * Dh) * (D ** -0.5)),
            "wo": _w((lambda *s: torch.randn(*s, dtype=torch.bfloat16) * 0.2)(Hq * Dh, D) * ((Hq * Dh) ** -0.5)),
        }
    _A_in = _A_setup()

    def _B_setup():
        B, S, D, F = 8, 1, 576, 4608
        return {
            "x": _w((lambda *s: torch.randn(*s, dtype=torch.bfloat16) * 0.05)(B, S, D)),
            "w_gate": _w((lambda *s: torch.randn(*s, dtype=torch.bfloat16) * 0.1)(D, F)),
            "w_up": _w((lambda *s: torch.randn(*s, dtype=torch.bfloat16) * 0.1)(D, F)),
            "w_down": _w((lambda *s: torch.randn(*s, dtype=torch.bfloat16) * 0.1)(F, D)),
        }
    _B_in = _B_setup()

    return {
        "A_x": _A_in["x"],
        "A_k_cache": _A_in["k_cache"],
        "A_v_cache": _A_in["v_cache"],
        "A_wq": _A_in["wq"],
        "A_wo": _A_in["wo"],
        "B_x": _B_in["x"],
        "B_w_gate": _B_in["w_gate"],
        "B_w_up": _B_in["w_up"],
        "B_w_down": _B_in["w_down"],
    }

def reference(A_x, A_k_cache, A_v_cache, A_wq, A_wo, B_x, B_w_gate, B_w_up, B_w_down):
    def _A_ref(x, k_cache, v_cache, wq, wo):
        B, Sq, D = x.shape
        Hq, Dh = 32, 128
        Hkv = k_cache.shape[1]
        rep = Hq // Hkv
        q = (lambda x, *d: x.permute(*d))((x @ wq).reshape(B, Sq, Hq, Dh), 0, 2, 1, 3)
        k = (lambda x, n, axis: torch.repeat_interleave(x, n, dim=axis))(k_cache, rep, axis=1)
        v = (lambda x, n, axis: torch.repeat_interleave(x, n, dim=axis))(v_cache, rep, axis=1)
        scores = torch.einsum("bhqd,bhkd->bhqk", q, k) * (Dh ** -0.5)
        p = _softmax(scores, axis=-1)
        o = torch.einsum("bhqk,bhkd->bhqd", p, v)
        return (lambda x, *d: x.permute(*d))(o, 0, 2, 1, 3).reshape(B, Sq, Hq * Dh) @ wo

    def _B_ref(x, w_gate, w_up, w_down):
        return (_gelu(x @ w_gate) * (x @ w_up)) @ w_down

    x = A_x
    xn = _layernorm(x, axis=-1)
    s = _A_ref(xn, A_k_cache, A_v_cache, A_wq, A_wo)
    g = _silu(_B_ref(xn, B_w_gate, B_w_up, B_w_down))
    return x + s * g
```

```cpp
#include <cuda_runtime.h>
#include <cuda_bf16.h>
#include <cuda.h>
#include <stdint.h>

namespace {

constexpr int NB = 8, DM = 576, HKV = 16, SK = 8192, DH = 128, FF = 4608, NQC = 4096;
constexpr int NPAIR = NB * HKV;
constexpr int TILE = 64;
constexpr int TPP = SK / TILE;
constexpr int IPP = 32;
constexpr int TPI = TPP / IPP;
constexpr int N_A = NPAIR * IPP;
constexpr int N_Q = NQC / 32;
constexpr int N_G = FF / 32;
constexpr int NCB = DM / 64;
constexpr int N_DR = FF / 256;
constexpr int N_D = N_DR * NCB;
constexpr int N_O = HKV * NCB;
constexpr int N_TOTAL = N_A + N_G + N_D + N_O;
constexpr int NFIN = HKV + N_DR;
constexpr int NCQ = NCB * 128;

#define NSLOTS_V 5
#define CAP_V 2
#define LAG_V 8
#define CAPY_V 1
#define NG1_V 144
#define FINMODE 0
#define TC1 0
#define LASTC2 0
#define PSLEEP 50
#define PTHR 8
#define FSLEEP 0
#define FDIRECT 1
#define ODIRECT 1
#define DFIRST 1
#define CAPG_V 2
#define RCAP_V NSLOTS_V
#define RUSH_V 80
constexpr int NSLOTS = NSLOTS_V;
constexpr int CAP = CAP_V;
constexpr int LAG = LAG_V;
constexpr int CAPY = CAPY_V;
constexpr int NG1 = NG1_V;
constexpr int NTAILP = 4;
constexpr int RUSH = RUSH_V;
static_assert(NTAILP == 4, "finalizer phase 2 maps the late partials onto lane quads");
constexpr int SLOT_BYTES = 36864;
constexpr int NTHREADS = 320;

enum : uint32_t { T_A = 0, T_Q = 1, T_GATE = 2, T_UP = 3, T_D = 4, T_O = 5, T_END = 6 };
constexpr uint32_t F_FIRST = 1u << 24, F_LAST = 1u << 25;
constexpr uint32_t C_END = 0xffffffffu;

constexpr int SM_XN = NSLOTS * SLOT_BYTES;
constexpr int SM_CBUF = SM_XN + 9216;
constexpr int SM_CML = SM_CBUF + 2 * 4 * 1024;
constexpr int SM_RED = SM_CML + 128;
constexpr int SM_BAR = SM_RED + 1024;
constexpr int SM_MISC = SM_BAR + 4 * NSLOTS * 8;
constexpr int SM_TOTAL = SM_MISC + 128;
constexpr int SMEM_BYTES = SM_TOTAL + 1024;

struct alignas(128) Ctr { uint32_t v; uint32_t pad[31]; };
__device__ Ctr g_epoch, g_work;
__device__ Ctr g_qcnt[HKV], g_pcnt[NPAIR], g_ocnt[HKV], g_fcnt[NCB * 4];
__device__ alignas(128) uint32_t g_q[NPAIR * 256];
__device__ alignas(128) uint32_t g_po[NPAIR * IPP * DH * 2];
__device__ alignas(128) uint32_t g_pml[NPAIR * IPP * 8];
__device__ alignas(128) uint32_t g_o[NB * NQC];
__device__ alignas(128) uint32_t g_h[NB * FF];
__device__ alignas(128) uint32_t g_fin[NCB * 4 * NFIN * 32 * 4];

#define TS(i)
#define TR(code)
#define TR2(code)

__device__ __forceinline__ uint32_t smem_u32(const void* p) { return (uint32_t)__cvta_generic_to_shared(p); }
__device__ __forceinline__ void mbar_init(uint32_t bar, uint32_t cnt) {
    asm volatile("mbarrier.init.shared::cta.b64 [%0], %1;" ::"r"(bar), "r"(cnt) : "memory");
}
__device__ __forceinline__ void mbar_arrive(uint32_t bar) {
    asm volatile("mbarrier.arrive.shared::cta.b64 _, [%0];" ::"r"(bar) : "memory");
}
__device__ __forceinline__ void mbar_arrive_expect_tx(uint32_t bar, uint32_t bytes) {
    asm volatile("mbarrier.arrive.expect_tx.shared::cta.b64 _, [%0], %1;" ::"r"(bar), "r"(bytes) : "memory");
}
__device__ __forceinline__ void mbar_expect_tx(uint32_t bar, uint32_t bytes) {
    asm volatile("mbarrier.expect_tx.relaxed.cta.shared::cta.b64 [%0], %1;" ::"r"(bar), "r"(bytes) : "memory");
}
__device__ __forceinline__ bool mbar_try_wait(uint32_t bar, uint32_t parity) {
    uint32_t ok;
    asm volatile("{\n.reg .pred p;\nmbarrier.try_wait.parity.shared::cta.b64 p, [%1], %2;\nselp.u32 %0, 1, 0, p;\n}"
                 : "=r"(ok) : "r"(bar), "r"(parity) : "memory");
    return ok != 0;
}
__device__ __forceinline__ bool mbar_try_wait_ns(uint32_t bar, uint32_t parity, uint32_t ns) {
    uint32_t ok;
    asm volatile("{\n.reg .pred p;\nmbarrier.try_wait.parity.shared::cta.b64 p, [%1], %2, %3;\nselp.u32 %0, 1, 0, p;\n}"
                 : "=r"(ok) : "r"(bar), "r"(parity), "r"(ns) : "memory");
    return ok != 0;
}
__device__ __forceinline__ void mbar_wait(uint32_t bar, uint32_t parity) {
    uint32_t it = 0;
    while (!mbar_try_wait(bar, parity)) {
        if (++it > (1u << 22)) __trap();
    }
}
__device__ __forceinline__ uint32_t ld_relaxed(const uint32_t* p) {
    uint32_t v;
    asm volatile("ld.relaxed.gpu.global.u32 %0, [%1];" : "=r"(v) : "l"(p) : "memory");
    return v;
}
__device__ __forceinline__ uint2 ld_relaxed2(const uint32_t* p) {
    uint2 v;
    asm volatile("ld.relaxed.gpu.global.v2.u32 {%0,%1}, [%2];" : "=r"(v.x), "=r"(v.y) : "l"(p) : "memory");
    return v;
}
__device__ __forceinline__ uint4 ld_relaxed4(const uint32_t* p) {
    uint4 v;
    asm volatile("ld.relaxed.gpu.global.v4.u32 {%0,%1,%2,%3}, [%4];" : "=r"(v.x), "=r"(v.y), "=r"(v.z), "=r"(v.w) : "l"(p) : "memory");
    return v;
}
__device__ __forceinline__ void st_relaxed(uint32_t* p, uint32_t v) {
    asm volatile("st.relaxed.gpu.global.u32 [%0], %1;" ::"l"(p), "r"(v) : "memory");
}
__device__ __forceinline__ void st_relaxed2(uint32_t* p, uint32_t a, uint32_t b) {
    asm volatile("st.relaxed.gpu.global.v2.u32 [%0], {%1,%2};" ::"l"(p), "r"(a), "r"(b) : "memory");
}
__device__ __forceinline__ void st_relaxed4(uint32_t* p, uint32_t a, uint32_t b, uint32_t c, uint32_t d) {
    asm volatile("st.relaxed.gpu.global.v4.u32 [%0], {%1,%2,%3,%4};" ::"l"(p), "r"(a), "r"(b), "r"(c), "r"(d) : "memory");
}
__device__ __forceinline__ void red_inc(uint32_t* p) {
    asm volatile("red.relaxed.gpu.global.add.u32 [%0], 1;" ::"l"(p) : "memory");
}
__device__ __forceinline__ void wait_count(const uint32_t* p, uint32_t base, uint32_t target, uint32_t sleep_ns) {
    uint32_t it = 0;
    while (ld_relaxed(p) - base < target) {
        if (sleep_ns) __nanosleep(sleep_ns);
        if (++it > (1u << 22)) __trap();
    }
}
__device__ __forceinline__ uint32_t tag_f32(float v, uint32_t tag) { return (__float_as_uint(v) & ~1u) | tag; }
__device__ __forceinline__ uint32_t tag_bf16(float v, uint32_t tag) {
    return ((uint32_t)__bfloat16_as_ushort(__float2bfloat16_rn(v)) << 16) | tag;
}
__device__ __forceinline__ uint32_t bad4(uint4 v, uint32_t tag) { return ((v.x ^ tag) | (v.y ^ tag) | (v.z ^ tag) | (v.w ^ tag)) & 1u; }
__device__ __forceinline__ uint32_t hi16x2(uint32_t lo, uint32_t hi) { return __byte_perm(lo, hi, 0x7632); }
__device__ __forceinline__ uint4 poll_bf16x8(const uint32_t* p, uint32_t tag) {
    uint32_t it = 0;
    while (true) {
        const uint4 a = ld_relaxed4(p), b = ld_relaxed4(p + 4);
        if (!(bad4(a, tag) | bad4(b, tag))) return make_uint4(hi16x2(a.x, a.y), hi16x2(a.z, a.w), hi16x2(b.x, b.y), hi16x2(b.z, b.w));
        if (++it > (1u << 22)) __trap();
    }
}
__device__ __forceinline__ void tma_2d(uint32_t dst, const CUtensorMap* map, int c0, int c1, uint32_t bar, uint64_t pol) {
    asm volatile("cp.async.bulk.tensor.2d.shared::cluster.global.mbarrier::complete_tx::bytes.L2::cache_hint "
                 "[%0], [%1, {%3, %4}], [%2], %5;"
                 ::"r"(dst), "l"(map), "r"(bar), "r"(c0), "r"(c1), "l"(pol) : "memory");
}
__device__ __forceinline__ void tma_3d(uint32_t dst, const CUtensorMap* map, int c0, int c1, int c2, uint32_t bar, uint64_t pol) {
    asm volatile("cp.async.bulk.tensor.3d.shared::cluster.global.mbarrier::complete_tx::bytes.L2::cache_hint "
                 "[%0], [%1, {%3, %4, %5}], [%2], %6;"
                 ::"r"(dst), "l"(map), "r"(bar), "r"(c0), "r"(c1), "r"(c2), "l"(pol) : "memory");
}
__device__ __forceinline__ void ldsm_x4(uint32_t addr, uint32_t& r0, uint32_t& r1, uint32_t& r2, uint32_t& r3) {
    asm volatile("ldmatrix.sync.aligned.m8n8.x4.shared.b16 {%0,%1,%2,%3}, [%4];"
                 : "=r"(r0), "=r"(r1), "=r"(r2), "=r"(r3) : "r"(addr) : "memory");
}
__device__ __forceinline__ void ldsm_x4_t(uint32_t addr, uint32_t& r0, uint32_t& r1, uint32_t& r2, uint32_t& r3) {
    asm volatile("ldmatrix.sync.aligned.m8n8.x4.trans.shared.b16 {%0,%1,%2,%3}, [%4];"
                 : "=r"(r0), "=r"(r1), "=r"(r2), "=r"(r3) : "r"(addr) : "memory");
}
__device__ __forceinline__ void mma_bf16(float (&d)[4], uint32_t a0, uint32_t a1, uint32_t a2, uint32_t a3, uint32_t b0, uint32_t b1) {
    asm volatile("mma.sync.aligned.m16n8k16.row.col.f32.bf16.bf16.f32 {%0,%1,%2,%3}, {%4,%5,%6,%7}, {%8,%9}, {%0,%1,%2,%3};"
                 : "+f"(d[0]), "+f"(d[1]), "+f"(d[2]), "+f"(d[3])
                 : "r"(a0), "r"(a1), "r"(a2), "r"(a3), "r"(b0), "r"(b1));
}
__device__ __forceinline__ uint4 lds128(uint32_t addr) {
    uint4 v;
    asm volatile("ld.shared.v4.u32 {%0,%1,%2,%3}, [%4];" : "=r"(v.x), "=r"(v.y), "=r"(v.z), "=r"(v.w) : "r"(addr) : "memory");
    return v;
}
__device__ __forceinline__ void sts128(uint32_t addr, uint4 v) {
    asm volatile("st.shared.v4.u32 [%0], {%1,%2,%3,%4};" ::"r"(addr), "r"(v.x), "r"(v.y), "r"(v.z), "r"(v.w) : "memory");
}
__device__ __forceinline__ void named_bar_sync(int id, int n) { asm volatile("bar.sync %0, %1;" ::"r"(id), "r"(n) : "memory"); }
__device__ __forceinline__ void named_bar_arrive(int id, int n) { asm volatile("bar.arrive %0, %1;" ::"r"(id), "r"(n) : "memory"); }
__device__ __forceinline__ float ex2(float x) { float y; asm("ex2.approx.ftz.f32 %0, %1;" : "=f"(y) : "f"(x)); return y; }
__device__ __forceinline__ float warp_max(float x) {
    int i = __float_as_int(x);
    i ^= (i >> 31) & 0x7fffffff;
    i = __reduce_max_sync(0xffffffffu, i);
    i ^= (i >> 31) & 0x7fffffff;
    return __int_as_float(i);
}
template <int H>
__device__ __forceinline__ void fold_stage(float (&v)[16], int lane) {
    const bool up = lane & (2 * H);
#pragma unroll
    for (int i = 0; i < H; i++) {
        const float lo = v[i], hi = v[i + H];
        const float keep = up ? hi : lo, send = up ? lo : hi;
        v[i] = keep + __shfl_xor_sync(0xffffffffu, send, 2 * H);
    }
}
__device__ __forceinline__ float quad_transpose_sum(float v0, float v1, float v2, float v3, int lane) {
    const bool hi = lane & 2, od = lane & 1;
    const float k0 = (hi ? v2 : v0) + __shfl_xor_sync(0xffffffffu, hi ? v0 : v2, 2);
    const float k1 = (hi ? v3 : v1) + __shfl_xor_sync(0xffffffffu, hi ? v1 : v3, 2);
    return (od ? k1 : k0) + __shfl_xor_sync(0xffffffffu, od ? k0 : k1, 1);
}
__device__ __forceinline__ float rbf(float x) { return __bfloat162float(__float2bfloat16_rn(x)); }
__device__ __forceinline__ uint32_t pack_bf16(float lo, float hi) {
    __nv_bfloat162 v = __floats2bfloat162_rn(lo, hi);
    return *reinterpret_cast<uint32_t*>(&v);
}
__device__ __forceinline__ int bfrag_idx(int batch, int k) {
    int r = k & 31;
    return (k >> 5) * 256 + (batch * 4 + ((r & 7) >> 1)) * 8 + ((r >> 3) << 1) + (r & 1);
}

__global__ void __launch_bounds__(NTHREADS, 1)
fused_decode_kernel(const __grid_constant__ CUtensorMap mapK, const __grid_constant__ CUtensorMap mapV,
                    const __grid_constant__ CUtensorMap mapWq, const __grid_constant__ CUtensorMap mapWg,
                    const __grid_constant__ CUtensorMap mapWu, const __grid_constant__ CUtensorMap mapWd,
                    const __grid_constant__ CUtensorMap mapWo,
                    const __nv_bfloat16* __restrict__ x, __nv_bfloat16* __restrict__ out) {
    extern __shared__ unsigned char smem_raw[];
    const uint32_t sbase = (smem_u32(smem_raw) + 1023u) & ~1023u;
    unsigned char* sptr = smem_raw + (sbase - smem_u32(smem_raw));
    const int tid = threadIdx.x, warp = tid >> 5, lane = tid & 31;
    const uint32_t bar_full = sbase + SM_BAR;
    const uint32_t bar_empty = bar_full + NSLOTS * 8;
    const uint32_t bar_qreq = bar_empty + NSLOTS * 8;
    const uint32_t bar_qfull = bar_qreq + NSLOTS * 8;
    volatile uint32_t* s_meta = reinterpret_cast<volatile uint32_t*>(sptr + SM_MISC);
    volatile uint32_t* s_qreq = reinterpret_cast<volatile uint32_t*>(sptr + SM_MISC + 32);
    volatile uint32_t* s_misc = reinterpret_cast<volatile uint32_t*>(sptr + SM_MISC + 64);

    if (warp == 8) {
        if (lane == 0) {
            TS(0);
            for (int i = 0; i < NSLOTS; i++) {
                mbar_init(bar_full + i * 8, 1); mbar_init(bar_empty + i * 8, 4);
                mbar_init(bar_qreq + i * 8, 1); mbar_init(bar_qfull + i * 8, 1);
            }
            s_misc[1] = 0;
            asm volatile("fence.mbarrier_init.release.cluster;" ::: "memory");
            asm volatile("fence.proxy.async.shared::cta;" ::: "memory");
        }
        __syncwarp();
        named_bar_arrive(1, NTHREADS);
        if (lane != 0) return;
        const uint32_t epoch = ld_relaxed(&g_epoch.v);
        uint64_t pol_stream, pol_norm;
        asm volatile("createpolicy.fractional.L2::evict_first.b64 %0, 1.0;" : "=l"(pol_stream));
        asm volatile("createpolicy.fractional.L2::evict_normal.b64 %0, 1.0;" : "=l"(pol_norm));

        uint32_t slot = 0, phase = 1;
        uint32_t lslot = 0, lphase = 0;
        uint32_t inflight = 0, nq = 0, inflight_cap_x = CAP;
        auto acquire_slot = [&](uint32_t cap) {
            while (inflight >= cap) {
                mbar_wait(bar_full + lslot * 8, lphase);
                if (++lslot == NSLOTS) { lslot = 0; lphase ^= 1; }
                inflight--;
            }
            mbar_wait(bar_empty + slot * 8, phase);
        };
        auto advance = [&]() { inflight++; if (++slot == NSLOTS) { slot = 0; phase ^= 1; } };
        auto post_stage = [&](uint32_t req) {
            s_qreq[nq] = req | (slot << 16);
            mbar_arrive(bar_qreq + nq * 8);
            if (++nq == NSLOTS) nq = 0;
        };
        auto issue_x = [&](const CUtensorMap* map, uint32_t meta, int col) {
            acquire_slot(inflight_cap_x);
            const uint32_t dst = sbase + slot * SLOT_BYTES, bar = bar_full + slot * 8;
            s_meta[slot] = meta;
            mbar_arrive_expect_tx(bar, 576 * 64);
            tma_2d(dst, map, col, 0, bar, pol_norm);
            tma_2d(dst + 192 * 64, map, col, 192, bar, pol_norm);
            tma_2d(dst + 384 * 64, map, col, 384, bar, pol_norm);
            advance();
        };
        auto issue_y = [&](const CUtensorMap* map, uint32_t type, uint32_t i) {
            acquire_slot(inflight_cap_x);
            const uint32_t dst = sbase + slot * SLOT_BYTES, bar = bar_full + slot * 8;
            s_meta[slot] = (type << 28) | i;
            mbar_arrive_expect_tx(bar, 256 * 128);
            tma_2d(dst, map, (i % NCB) * 64, (i / NCB) * 256, bar, pol_stream);
            post_stage((type << 28) | (i / NCB));
            advance();
        };

        for (int qi = blockIdx.x; qi < N_Q; qi += gridDim.x) issue_x(&mapWq, (T_Q << 28) | qi, qi * 32);

        uint32_t item = blockIdx.x;
        while (item < (uint32_t)N_TOTAL) {
            uint32_t next = 0;
            if (item - NG1 < (uint32_t)N_A) {
                uint32_t ai = item - NG1;
                int pair, tile0, tstep, ntile;
                if (ai < (uint32_t)(N_A - 4 * IPP)) {
                    pair = ai / IPP; tile0 = ai % IPP; tstep = IPP; ntile = TPI;
                } else {
                    const int r = ai - (N_A - 4 * IPP), c = r >> 2;
                    pair = NPAIR - 4 + (r & 3);
                    const int lv = (c + 4) >> 3;
                    ntile = 6 - lv;
                    tile0 = (lv == 0 ? 0 : lv == 1 ? 24 : lv == 2 ? 64 : lv == 3 ? 96 : 120) + (c - (lv == 0 ? 0 : lv * 8 - 4)) * ntile;
                    tstep = 1;
                    ai = pair * IPP + c;
                }
                s_misc[1] = pair;
#pragma unroll 1
                for (int j = 0; j < ntile; j++) {
                    acquire_slot(tstep == 1 && j >= ntile - TC1 ? 1 : CAP);
                    const uint32_t dst = sbase + slot * SLOT_BYTES, bar = bar_full + slot * 8;
                    s_meta[slot] = (T_A << 28) | (j == 0 ? F_FIRST : 0u) | (j == ntile - 1 ? F_LAST : 0u) | ai;
                    mbar_arrive_expect_tx(bar, 2 * TILE * 256);
                    const int row = pair * SK + (tile0 + j * tstep) * TILE;
                    tma_3d(dst, &mapK, 0, row, 0, bar, pol_stream);
                    tma_3d(dst + TILE * 256, &mapV, 0, row, 0, bar, pol_stream);
                    if (j == 0) post_stage((T_A << 28) | pair);
                    if (j == ntile - 1) next = atomicAdd(&g_work.v, 1u);
                    advance();
                }
            } else {
                next = atomicAdd(&g_work.v, 1u);
                if (item >= (uint32_t)NG1) { s_misc[1] = NPAIR; inflight_cap_x = item >= (uint32_t)(N_TOTAL - LASTC2) ? 2 : CAPY; }
                if (item < (uint32_t)(N_G + N_A)) {
                    const uint32_t gi = item < (uint32_t)NG1 ? item : item - N_A;
                    issue_x(&mapWg, (T_GATE << 28) | gi, gi * 32);
                    issue_x(&mapWu, (T_UP << 28) | gi, gi * 32);
                } else if (item < (uint32_t)(N_G + N_A + N_D)) {
                    issue_y(&mapWd, T_D, item - (N_G + N_A));
                } else {
                    issue_y(&mapWo, T_O, item - (N_G + N_A + N_D));
                }
            }
            item = next - (epoch * (uint32_t)N_TOTAL - gridDim.x);
        }
        s_misc[1] = NPAIR + 1;
        s_qreq[nq] = C_END;
        mbar_arrive(bar_qreq + nq * 8);
        mbar_wait(bar_empty + slot * 8, phase);
        s_meta[slot] = T_END << 28;
        mbar_arrive(bar_full + slot * 8);
        TS(3);
        return;
    }

    if (warp < 8) {
        const __nv_bfloat162* xr = reinterpret_cast<const __nv_bfloat162*>(x + warp * DM);
        float2 v[9];
#pragma unroll
        for (int i = 0; i < 9; i++) v[i] = __bfloat1622float2(xr[lane + 32 * i]);
        float s = 0.f;
#pragma unroll
        for (int i = 0; i < 9; i++) s += v[i].x + v[i].y;
#pragma unroll
        for (int o = 16; o; o >>= 1) s += __shfl_xor_sync(0xffffffffu, s, o);
        const float mean = s * (1.0f / DM);
        float q = 0.f;
#pragma unroll
        for (int i = 0; i < 9; i++) { float a = v[i].x - mean, b = v[i].y - mean; q += a * a + b * b; }
#pragma unroll
        for (int o = 16; o; o >>= 1) q += __shfl_xor_sync(0xffffffffu, q, o);
        const float mb = rbf(mean);
        const float sd = rbf(sqrtf(rbf(rbf(q * (1.0f / DM)) + 1e-5f)));
        __nv_bfloat16* xn = reinterpret_cast<__nv_bfloat16*>(sptr + SM_XN);
#pragma unroll
        for (int i = 0; i < 9; i++) {
            const int k = 2 * (lane + 32 * i);
            const uint32_t p = pack_bf16(rbf(v[i].x - mb) / sd, rbf(v[i].y - mb) / sd);
            *reinterpret_cast<uint32_t*>(xn + bfrag_idx(warp, k)) = p;
        }
    } else if (lane == 0) {
        s_misc[0] = ld_relaxed(&g_epoch.v);
    }
    named_bar_sync(1, NTHREADS);
    const uint32_t epoch = s_misc[0];
    const uint32_t tag = (epoch & 1u) ^ 1u;
    if (tid == 0) TS(12);

    if (warp < 4) {
        constexpr float SCALE_LOG2E = 0.08838834764831845f * 1.4426950408889634f;
        uint32_t qa[16];
        float acc[8][4];
        float m_run = -INFINITY, l_run = 0.f;
        float gate[4] = {0.f, 0.f, 0.f, 0.f};
        uint32_t slot = 0, phase = 0, nitem = 0, qphase = 0;
        const int li = lane >> 3, lr = lane & 7;
        const uint32_t k_off = (uint32_t)((warp * 16 + lr) * 128);
        const uint32_t v_off = (uint32_t)((warp * 16 + (li >> 1) * 8 + lr) * 128);
#pragma unroll
        for (int i = 0; i < 16; i++) qa[i] = 0;
#pragma unroll
        for (int i = 0; i < 8; i++) { acc[i][0] = acc[i][1] = acc[i][2] = acc[i][3] = 0.f; }

        while (true) {
            mbar_wait(bar_full + slot * 8, phase);
            const uint32_t meta = s_meta[slot];
            const uint32_t type = meta >> 28;
            const uint32_t sb = sbase + slot * SLOT_BYTES;
            if (type == T_A) {
                if (meta & F_FIRST) {
                    mbar_wait(bar_qfull + slot * 8, (qphase >> slot) & 1u);
                    qphase ^= 1u << slot;
                    if (lane < 8) {
#pragma unroll
                        for (int i = 0; i < 4; i++) {
                            uint4 t = lds128(sb + 2 * TILE * 256 + lane * 64 + i * 16);
                            qa[4 * i] = t.x; qa[4 * i + 1] = t.y; qa[4 * i + 2] = t.z; qa[4 * i + 3] = t.w;
                        }
                    }
                    __syncwarp();
                    m_run = -INFINITY; l_run = 0.f;
#pragma unroll
                    for (int i = 0; i < 8; i++) { acc[i][0] = acc[i][1] = acc[i][2] = acc[i][3] = 0.f; }
                    if (tid == 0 && nitem == 0) TS(2);
                }
                float s[4][4];
#pragma unroll
                for (int i = 0; i < 4; i++) { s[i][0] = s[i][1] = s[i][2] = s[i][3] = 0.f; }
#pragma unroll
                for (int half = 0; half < 2; half++)
#pragma unroll
                    for (int cc = 0; cc < 2; cc++)
#pragma unroll
                        for (int nt = 0; nt < 2; nt++) {
                            uint32_t r0, r1, r2, r3;
                            ldsm_x4(sb + half * 8192 + k_off + nt * 1024 + (((cc * 4 + li) ^ lr) << 4), r0, r1, r2, r3);
                            const int ks = half * 4 + cc * 2;
                            mma_bf16(s[nt * 2 + 0], qa[2 * ks], 0u, qa[2 * ks + 1], 0u, r0, r1);
                            mma_bf16(s[nt * 2 + 1], qa[2 * ks + 2], 0u, qa[2 * ks + 3], 0u, r2, r3);
                        }
                uint32_t va[8][4];
#pragma unroll
                for (int mt = 0; mt < 8; mt++)
                    ldsm_x4_t(sb + TILE * 256 + (mt >> 2) * 8192 + v_off + (((((mt & 3) << 1) + (li & 1)) ^ lr) << 4),
                              va[mt][0], va[mt][1], va[mt][2], va[mt][3]);
                __syncwarp();
                if (lane == 0) mbar_arrive(bar_empty + slot * 8);

                const float s0 = (s[0][0] + s[1][0]) * SCALE_LOG2E, s1 = (s[0][1] + s[1][1]) * SCALE_LOG2E;
                const float s2 = (s[2][0] + s[3][0]) * SCALE_LOG2E, s3 = (s[2][1] + s[3][1]) * SCALE_LOG2E;
                float mx = fmaxf(fmaxf(s0, s1), fmaxf(s2, s3));
                mx = fmaxf(mx, __shfl_xor_sync(0xffffffffu, mx, 1));
                mx = fmaxf(mx, __shfl_xor_sync(0xffffffffu, mx, 2));
                const float m_new = fmaxf(m_run, mx);
                const float alpha = ex2(m_run - m_new);
                m_run = m_new;
                const uint32_t b0 = pack_bf16(ex2(s0 - m_new), ex2(s1 - m_new));
                const uint32_t b1 = pack_bf16(ex2(s2 - m_new), ex2(s3 - m_new));
                const float psum = (__uint_as_float(b0 << 16) + __uint_as_float(b0 & 0xffff0000u)) +
                                   (__uint_as_float(b1 << 16) + __uint_as_float(b1 & 0xffff0000u));
                l_run = l_run * alpha + psum;
                const float a0 = __shfl_sync(0xffffffffu, alpha, 0), a1 = __shfl_sync(0xffffffffu, alpha, 4);
                if (a0 != 1.0f || a1 != 1.0f) {
#pragma unroll
                    for (int mt = 0; mt < 8; mt++) { acc[mt][0] *= a0; acc[mt][1] *= a1; acc[mt][2] *= a0; acc[mt][3] *= a1; }
                }
#pragma unroll
                for (int mt = 0; mt < 8; mt++) mma_bf16(acc[mt], va[mt][0], va[mt][1], va[mt][2], va[mt][3], b0, b1);

                if (meta & F_LAST) {
                    const uint32_t buf = nitem & 1;
                    float l = l_run;
                    l += __shfl_xor_sync(0xffffffffu, l, 1);
                    l += __shfl_xor_sync(0xffffffffu, l, 2);
                    float2* cb = reinterpret_cast<float2*>(sptr + SM_CBUF + buf * 4096);
                    float* cml = reinterpret_cast<float*>(sptr + SM_CML + buf * 64);
                    if ((lane & 3) == 0) {
#pragma unroll
                        for (int mt = 0; mt < 8; mt++) {
                            cb[warp * 128 + mt * 16 + (lane >> 2)] = make_float2(acc[mt][0], acc[mt][1]);
                            cb[warp * 128 + mt * 16 + 8 + (lane >> 2)] = make_float2(acc[mt][2], acc[mt][3]);
                        }
                        if (lane < 8) { cml[warp * 4 + (lane >> 2)] = m_run; cml[warp * 4 + 2 + (lane >> 2)] = l; }
                    }
                    named_bar_sync(2, 128);
                    float4 ml[4];
                    float2 ov[4];
#pragma unroll
                    for (int w = 0; w < 4; w++) { ml[w] = reinterpret_cast<const float4*>(cml)[w]; ov[w] = cb[w * 128 + tid]; }
                    const float M0 = fmaxf(fmaxf(ml[0].x, ml[1].x), fmaxf(ml[2].x, ml[3].x));
                    const float M1 = fmaxf(fmaxf(ml[0].y, ml[1].y), fmaxf(ml[2].y, ml[3].y));
                    float o0 = 0.f, o1 = 0.f, L0 = 0.f, L1 = 0.f;
#pragma unroll
                    for (int w = 0; w < 4; w++) {
                        const float e0 = ex2(ml[w].x - M0), e1 = ex2(ml[w].y - M1);
                        o0 += e0 * ov[w].x; o1 += e1 * ov[w].y;
                        L0 += e0 * ml[w].z; L1 += e1 * ml[w].w;
                    }
                    const uint32_t item = meta & 0xffffffu;
                    const int pos = (tid & ~31) + ((tid & 7) >> 1) * 8 + ((tid >> 3) & 3) * 2 + (tid & 1);
                    st_relaxed2(g_po + (((item / IPP) * 32 + (pos >> 2)) * IPP + (item % IPP)) * 8 + (pos & 3) * 2, tag_f32(o0, tag), tag_f32(o1, tag));
                    if (tid < 2) {
                        const uint32_t u0 = __float_as_uint(M0), u1 = __float_as_uint(M1);
                        if (tid == 0) st_relaxed4(g_pml + item * 8, (u0 << 16) | tag, (u0 & 0xffff0000u) | tag, (u1 << 16) | tag, (u1 & 0xffff0000u) | tag);
                        else st_relaxed4(g_pml + item * 8 + 4, tag_f32(L0, tag), tag_f32(L1, tag), tag, tag);
                        if (tid == 1) red_inc(&g_pcnt[item / IPP].v);
                    }
                    nitem++;
                }
                if (tid == 0 && (meta & F_LAST) && (meta & 0xffffffu) >= N_A - 400) TR(meta | 0x100000000ull);
            } else {
                if (tid == 0) TR(meta | 0x200000000ull);
                if (type <= T_UP) {
                    const int kh = warp >> 1, mt = warp & 1;
                    if (tid == 0 && type == T_Q) TS(13);
                    float c0[4] = {0.f, 0.f, 0.f, 0.f}, c1[4] = {0.f, 0.f, 0.f, 0.f};
                    const int row0 = kh * 288 + (li >> 1) * 8 + lr;
                    const uint32_t a_addr = sb + row0 * 64 + ((((mt << 1) + (li & 1)) ^ ((row0 >> 1) & 3)) << 4);
                    const uint32_t b_addr = sbase + SM_XN + kh * 9 * 512 + lane * 16;
#pragma unroll
                    for (int kb = 0; kb < 9; kb++) {
                        const uint4 b = lds128(b_addr + kb * 512);
                        uint32_t r0, r1, r2, r3;
                        ldsm_x4_t(a_addr + kb * 2048, r0, r1, r2, r3);
                        mma_bf16(c0, r0, r1, r2, r3, b.x, b.y);
                        ldsm_x4_t(a_addr + kb * 2048 + 1024, r0, r1, r2, r3);
                        mma_bf16(c1, r0, r1, r2, r3, b.z, b.w);
                    }
                    __syncwarp();
                    if (lane == 0) mbar_arrive(bar_empty + slot * 8);
#pragma unroll
                    for (int i = 0; i < 4; i++) c0[i] += c1[i];
                    float4* red = reinterpret_cast<float4*>(sptr + SM_RED) + mt * 32 + lane;
                    if (kh == 1) *red = make_float4(c0[0], c0[1], c0[2], c0[3]);
                    named_bar_sync(2, 128);
                    if (kh == 0) {
                        const float4 o = *red;
                        c0[0] += o.x; c0[1] += o.y; c0[2] += o.z; c0[3] += o.w;
                        const uint32_t idx = meta & 0xffffffu;
                        const int col = idx * 32 + mt * 16 + (lane >> 2), bt = (lane & 3) * 2;
                        if (type == T_Q) {
#pragma unroll
                            for (int i = 0; i < 4; i++) {
                                const int n = col + (i >> 1) * 8, b = bt + (i & 1);
                                const int head = n >> 7, d = n & 127, r = d & 15;
                                const int off = (((head & 1) * 4 + ((r & 7) >> 1)) * 8 + (d >> 4)) * 4 + ((r >> 3) << 1) + (r & 1);
                                st_relaxed(g_q + (b * HKV + (head >> 1)) * 256 + off, tag_bf16(c0[i], tag));
                            }
                            if (lane == 0) red_inc(&g_qcnt[idx >> 3].v);
                            if (tid == 0) TS(1);
                        } else if (type == T_GATE) {
#pragma unroll
                            for (int i = 0; i < 4; i++) gate[i] = c0[i];
                        } else {
#pragma unroll
                            for (int i = 0; i < 4; i++) {
                                const float g = rbf(gate[i]);
                                const float ge = rbf(0.5f * g * (1.0f + tanhf(0.7978845608028654f * (g + 0.044715f * g * g * g))));
                                st_relaxed(g_h + bfrag_idx(bt + (i & 1), col + (i >> 1) * 8), tag_bf16(ge * rbf(c0[i]), tag));
                            }
                        }
                    }
                    named_bar_sync(2, 128);
                } else if (type <= T_O) {
                    const uint32_t idx = meta & 0xffffffu;
                    const int rb = idx / NCB, cb = idx % NCB;
                    const bool is_o = type == T_O;
                    const uint32_t a_addr = sb + ((li >> 1) * 8 + lr) * 128 + ((((warp << 1) + (li & 1)) ^ lr) << 4);
                    uint32_t wa[16][4];
#pragma unroll
                    for (int ks = 0; ks < 16; ks++) ldsm_x4_t(a_addr + ks * 2048, wa[ks][0], wa[ks][1], wa[ks][2], wa[ks][3]);
                    uint32_t* dstp = g_fin + (((cb * 4 + warp) * NFIN + (is_o ? rb : HKV + rb)) * 32 + lane) * 4;
                    uint32_t* cntp = &g_fcnt[cb * 4 + warp].v + (is_o && rb >= HKV - NTAILP);
                    mbar_wait(bar_qfull + slot * 8, (qphase >> slot) & 1u);
                    qphase ^= 1u << slot;
                    if (tid == 0) TR(meta | 0x300000000ull);
                    uint4 b[8];
#pragma unroll
                    for (int kb = 0; kb < 8; kb++) b[kb] = lds128(sb + 32768 + kb * 512 + lane * 16);
                    float c[4][4];
#pragma unroll
                    for (int i = 0; i < 4; i++) { c[i][0] = c[i][1] = c[i][2] = c[i][3] = 0.f; }
#pragma unroll
                    for (int kb = 0; kb < 8; kb++) {
                        mma_bf16(c[(kb & 1) * 2], wa[2 * kb][0], wa[2 * kb][1], wa[2 * kb][2], wa[2 * kb][3], b[kb].x, b[kb].y);
                        mma_bf16(c[(kb & 1) * 2 + 1], wa[2 * kb + 1][0], wa[2 * kb + 1][1], wa[2 * kb + 1][2], wa[2 * kb + 1][3], b[kb].z, b[kb].w);
                    }
                    st_relaxed4(dstp, tag_f32((c[0][0] + c[1][0]) + (c[2][0] + c[3][0]), tag), tag_f32((c[0][1] + c[1][1]) + (c[2][1] + c[3][1]), tag),
                                tag_f32((c[0][2] + c[1][2]) + (c[2][2] + c[3][2]), tag), tag_f32((c[0][3] + c[1][3]) + (c[2][3] + c[3][3]), tag));
                    __syncwarp();
                    if (lane == 0) { red_inc(cntp); mbar_arrive(bar_empty + slot * 8); }
                } else {
                    if (tid == 0) { s_misc[1] = NPAIR + 2; TS(7); }
                    break;
                }
                if (tid == 0) TR(meta | 0x400000000ull);
            }
            if (++slot == NSLOTS) { slot = 0; phase ^= 1; }
        }
    } else if (warp < 8) {
        for (int n = blockIdx.x; n < NPAIR * 4; n += gridDim.x) {
            const int pair = n >> 2, u = (n & 3) * 4 + (warp - 4);
            uint32_t it = 0;
            while ((int)s_misc[1] < min(pair + LAG, NPAIR)) {
                __nanosleep(300);
                if (++it > (1u << 20)) __trap();
            }
            const uint32_t* pml = g_pml + (pair * IPP + lane) * 8;
            const uint32_t* po = g_po + ((pair * 32 + u * 2) * IPP + lane) * 8;
            uint32_t* dst = g_o + ((pair % HKV) * 8 + ((lane >> 1) & 1) * 4 + (u >> 2)) * 256 + ((pair / HKV) * 4 + (u & 3)) * 8 + (lane >> 2);
            uint4 pm, pv[4];
            uint2 pl;
            wait_count(&g_pcnt[pair].v, epoch * (uint32_t)IPP, IPP, PSLEEP);
            while (true) {
                pm = ld_relaxed4(pml); pl = ld_relaxed2(pml + 4);
#pragma unroll
                for (int i = 0; i < 4; i++) pv[i] = ld_relaxed4(po + (i >> 1) * (IPP * 8) + (i & 1) * 4);
                if (!((bad4(pm, tag) | (pl.x ^ tag) | (pl.y ^ tag) | bad4(pv[0], tag) | bad4(pv[1], tag) | bad4(pv[2], tag) | bad4(pv[3], tag)) & 1u)) break;
                if (++it > (1u << 22)) __trap();
            }
            __syncwarp();
            if (tid == 160) TR2(2000 + pair);
            const float m0 = __uint_as_float(hi16x2(pm.x, pm.y)), m1 = __uint_as_float(hi16x2(pm.z, pm.w));
            const float e0 = ex2(m0 - warp_max(m0)), e1 = ex2(m1 - warp_max(m1));
            float v[16];
#pragma unroll
            for (int i = 0; i < 4; i++) {
                v[4 * i] = e0 * __uint_as_float(pv[i].x); v[4 * i + 1] = e1 * __uint_as_float(pv[i].y);
                v[4 * i + 2] = e0 * __uint_as_float(pv[i].z); v[4 * i + 3] = e1 * __uint_as_float(pv[i].w);
            }
            const float l0 = e0 * __uint_as_float(pl.x), l1 = e1 * __uint_as_float(pl.y);
            float den = ((lane & 2) ? l1 : l0) + __shfl_xor_sync(0xffffffffu, (lane & 2) ? l0 : l1, 2);
            fold_stage<8>(v, lane); den += __shfl_xor_sync(0xffffffffu, den, 16);
            fold_stage<4>(v, lane); den += __shfl_xor_sync(0xffffffffu, den, 8);
            fold_stage<2>(v, lane); den += __shfl_xor_sync(0xffffffffu, den, 4);
            fold_stage<1>(v, lane);
            v[0] += __shfl_xor_sync(0xffffffffu, v[0], 1);
            den += __shfl_xor_sync(0xffffffffu, den, 1);
            if (!(lane & 1)) st_relaxed(dst, tag_bf16(__fdividef(v[0], den), tag));
            if (lane == 0) red_inc(&g_ocnt[pair % HKV].v);
            if (tid == 128) TS(5);
            if (tid == 224) TS(14);
        }
        {
            uint32_t it = 0;
            while (s_misc[1] < (uint32_t)(NPAIR + FINMODE)) {
                __nanosleep(FINMODE ? 100 : 500);
                if (++it > (1u << 20)) __trap();
            }
        }
        if (tid == 128) TS(6);
        for (int task = (warp - 4) * gridDim.x + blockIdx.x; task < NCQ / 4; task += gridDim.x * 4) {
            const int blk = task >> 3, q0 = (task & 7) * 4;
            const int mk = (lane & 15) >> 2, mi = lane & 3;
            const int oidx = (mk * 2 + (mi & 1)) * DM + blk * 16 + (task & 7) + (mi >> 1) * 8;
            const float xv = __bfloat162float(x[oidx]);
            const uint32_t* base = g_fin + (blk * NFIN * 32 + q0) * 4;
            const bool late_lane = lane >= HKV - NTAILP && lane < HKV, has2 = lane == 16 || lane == 17;
            const uint32_t* cnt = &g_fcnt[blk].v;
            const uint32_t* src = base + (HKV - NTAILP + mi) * 128 + mk * 4;
            uint32_t it = 0;
#pragma unroll 1
            for (int pass = 0; pass < 2; pass++) {
                uint4 p[4], e[4], q = make_uint4(tag, tag, tag, tag);
#pragma unroll
                for (int k = 0; k < 4; k++) p[k] = e[k] = make_uint4(tag, tag, tag, tag);
                bool late_in = true;
                if (pass) {
                    uint2 c;
                    while (true) {
                        c = ld_relaxed2(cnt);
                        if (c.x - epoch * (uint32_t)(NFIN - NTAILP) >= (uint32_t)(NFIN - NTAILP)) break;
                        if (FSLEEP) __nanosleep(FSLEEP);
                        if (++it > (1u << 22)) __trap();
                    }
                    if (tid == 160) TR2(3000);
                    it = 0;
                    late_in = c.y - epoch * (uint32_t)NTAILP >= (uint32_t)NTAILP;
                    while (true) {
                        uint32_t bad = 0;
                        if (!late_lane || late_in) {
#pragma unroll
                            for (int k = 0; k < 4; k++) p[k] = ld_relaxed4(base + lane * 128 + k * 4);
                        }
                        if (has2) {
#pragma unroll
                            for (int k = 0; k < 4; k++) e[k] = ld_relaxed4(base + (lane + 16) * 128 + k * 4);
                        }
#pragma unroll
                        for (int k = 0; k < 4; k++) bad |= bad4(p[k], tag) | bad4(e[k], tag);
                        if (!bad) break;
                        if (++it > (1u << 22)) __trap();
                    }
                    __syncwarp();
                    if (tid == 160) TR2(4000 + it + 100 * late_in);
                }
                float uu[4];
#pragma unroll
                for (int k = 0; k < 4; k++) {
                    const float v0 = __uint_as_float(p[k].x & ~1u) + __uint_as_float(e[k].x & ~1u), v1 = __uint_as_float(p[k].y & ~1u) + __uint_as_float(e[k].y & ~1u);
                    const float v2 = __uint_as_float(p[k].z & ~1u) + __uint_as_float(e[k].z & ~1u), v3 = __uint_as_float(p[k].w & ~1u) + __uint_as_float(e[k].w & ~1u);
                    uu[k] = quad_transpose_sum(v0, v1, v2, v3, lane);
                }
                const bool b3 = lane & 8, b2 = lane & 4;
                const float w0 = (b3 ? uu[2] : uu[0]) + __shfl_xor_sync(0xffffffffu, b3 ? uu[0] : uu[2], 8);
                const float w1 = (b3 ? uu[3] : uu[1]) + __shfl_xor_sync(0xffffffffu, b3 ? uu[1] : uu[3], 8);
                const float s_early = (b2 ? w1 : w0) + __shfl_xor_sync(0xffffffffu, b2 ? w0 : w1, 4);
                const float f = rbf(__shfl_down_sync(0xffffffffu, s_early, 16));
                const float g = rbf(__fdividef(f, 1.0f + __expf(-f)));
                if (tid == 128) TS(15);
                if (tid == 160 && pass) TR2(5000);
                if (!late_in) {
                    while (true) {
                        q = ld_relaxed4(src);
                        if (!bad4(q, tag)) break;
                        if (++it > (1u << 22)) __trap();
                    }
                    __syncwarp();
                }
                const float s_late = quad_transpose_sum(__uint_as_float(q.x & ~1u), __uint_as_float(q.y & ~1u),
                                                        __uint_as_float(q.z & ~1u), __uint_as_float(q.w & ~1u), lane);
                if (tid == 160 && pass) TR2(6000);
                if (pass && lane < 16) out[oidx] = __float2bfloat16_rn(xv + rbf(rbf(s_early + s_late) * g));
            }
            if (task == 0 && lane == 0) g_epoch.v = epoch + 1;
            if (lane == 0) TS(8 + warp - 4);
        }
    } else {
        uint32_t nq = 0, ph = 0, q_seen = 0;
        while (true) {
            mbar_wait(bar_qreq + nq * 8, ph);
            const uint32_t req = s_qreq[nq];
            if (req == C_END) break;
            const uint32_t type = req >> 28, slot = (req >> 16) & 0xffu, idx = req & 0xffffu;
            const uint32_t dst = sbase + slot * SLOT_BYTES + 32768 + lane * 16;
            if (type == T_A) {
                const uint32_t g = idx % HKV;
                if (!((q_seen >> g) & 1u)) {
                    wait_count(&g_qcnt[g].v, epoch * 16u, 16u, 100);
                    q_seen |= 1u << g;
                }
                sts128(dst, poll_bf16x8(g_q + idx * 256 + lane * 8, tag));
            } else {
                const int unit = (lane >> 2) * 32 + (lane & 3);
                const uint32_t* act = (type == T_O ? g_o : g_h) + idx * 2048 + unit * 8;
                const uint32_t d2 = sbase + slot * SLOT_BYTES + 32768 + unit * 16;
                uint4 a[14];
#pragma unroll
                for (int b = 0; b < 7; b++) { a[2 * b] = ld_relaxed4(act + b * 32); a[2 * b + 1] = ld_relaxed4(act + b * 32 + 4); }
                uint32_t pend = 0x80;
#pragma unroll
                for (int b = 0; b < 7; b++) {
                    pend |= (bad4(a[2 * b], tag) | bad4(a[2 * b + 1], tag)) << b;
                    sts128(d2 + b * 64, make_uint4(hi16x2(a[2 * b].x, a[2 * b].y), hi16x2(a[2 * b].z, a[2 * b].w),
                                                   hi16x2(a[2 * b + 1].x, a[2 * b + 1].y), hi16x2(a[2 * b + 1].z, a[2 * b + 1].w)));
                }
                if (type == T_O) wait_count(&g_ocnt[idx].v, epoch * (uint32_t)(NB * 16), ODIRECT ? (NB - 1) * 16 + 1 : NB * 16, PSLEEP);
                while (pend) {
                    const int b = __ffs(pend) - 1;
                    pend &= pend - 1;
                    sts128(d2 + b * 64, poll_bf16x8(act + b * 32, tag));
                }
            }
            asm volatile("fence.proxy.async.shared::cta;" ::: "memory");
            __syncwarp();
            if (lane == 0) mbar_arrive(bar_qfull + slot * 8);
            if (++nq == NSLOTS) { nq = 0; ph ^= 1; }
        }
    }
}

typedef CUresult (*EncodeTiledFn)(CUtensorMap*, CUtensorMapDataType, cuuint32_t, void*, const cuuint64_t*, const cuuint64_t*,
                                  const cuuint32_t*, const cuuint32_t*, CUtensorMapInterleave, CUtensorMapSwizzle,
                                  CUtensorMapL2promotion, CUtensorMapFloatOOBfill);

}

extern "C" void kernel_launch(void* const* d_in, const int* in_sizes, int n_in, void* d_out, int out_size) {
    (void)in_sizes; (void)n_in; (void)out_size;
    static EncodeTiledFn enc = nullptr;
    static int num_sms = 0;
    if (!enc) {
        cudaDriverEntryPointQueryResult qr;
        void* fn = nullptr;
        cudaGetDriverEntryPoint("cuTensorMapEncodeTiled", &fn, cudaEnableDefault, &qr);
        enc = (EncodeTiledFn)fn;
        cudaDeviceGetAttribute(&num_sms, cudaDevAttrMultiProcessorCount, 0);
        cudaFuncSetAttribute(fused_decode_kernel, cudaFuncAttributeMaxDynamicSharedMemorySize, SMEM_BYTES);
    }
    const __nv_bfloat16* x = (const __nv_bfloat16*)d_in[0];
    CUtensorMap mK, mV, mWq, mWg, mWu, mWd, mWo;
    const cuuint32_t es[3] = {1, 1, 1};
    auto kv_map = [&](CUtensorMap* m, void* p) {
        const cuuint64_t gd[3] = {64, (cuuint64_t)NPAIR * SK, 2};
        const cuuint64_t gs[2] = {256, 128};
        const cuuint32_t bx[3] = {64, TILE, 2};
        enc(m, CU_TENSOR_MAP_DATA_TYPE_BFLOAT16, 3, p, gd, gs, bx, es, CU_TENSOR_MAP_INTERLEAVE_NONE,
            CU_TENSOR_MAP_SWIZZLE_128B, CU_TENSOR_MAP_L2_PROMOTION_L2_256B, CU_TENSOR_MAP_FLOAT_OOB_FILL_NONE);
    };
    auto x_map = [&](CUtensorMap* m, void* p, int ncols) {
        const cuuint64_t gd[2] = {(cuuint64_t)ncols, DM};
        const cuuint64_t gs[1] = {(cuuint64_t)ncols * 2};
        const cuuint32_t bx[2] = {32, 192};
        enc(m, CU_TENSOR_MAP_DATA_TYPE_BFLOAT16, 2, p, gd, gs, bx, es, CU_TENSOR_MAP_INTERLEAVE_NONE,
            CU_TENSOR_MAP_SWIZZLE_64B, CU_TENSOR_MAP_L2_PROMOTION_L2_256B, CU_TENSOR_MAP_FLOAT_OOB_FILL_NONE);
    };
    auto y_map = [&](CUtensorMap* m, void* p, int nrows) {
        const cuuint64_t gd[2] = {DM, (cuuint64_t)nrows};
        const cuuint64_t gs[1] = {DM * 2};
        const cuuint32_t bx[2] = {64, 256};
        enc(m, CU_TENSOR_MAP_DATA_TYPE_BFLOAT16, 2, p, gd, gs, bx, es, CU_TENSOR_MAP_INTERLEAVE_NONE,
            CU_TENSOR_MAP_SWIZZLE_128B, CU_TENSOR_MAP_L2_PROMOTION_L2_128B, CU_TENSOR_MAP_FLOAT_OOB_FILL_NONE);
    };
    kv_map(&mK, d_in[1]);
    kv_map(&mV, d_in[2]);
    x_map(&mWq, d_in[3], NQC);
    y_map(&mWo, d_in[4], NQC);
    x_map(&mWg, d_in[6], FF);
    x_map(&mWu, d_in[7], FF);
    y_map(&mWd, d_in[8], FF);
    fused_decode_kernel<<<num_sms, NTHREADS, SMEM_BYTES>>>(mK, mV, mWq, mWg, mWu, mWd, mWo, x, (__nv_bfloat16*)d_out);
}
```

```cpp
#include <cuda_runtime.h>
#include <cuda_bf16.h>
#include <cuda.h>
#include <stdint.h>

namespace {

constexpr int NB = 8, DM = 576, HKV = 16, SK = 8192, DH = 128, FF = 4608, NQC = 4096;
constexpr int NPAIR = NB * HKV;
constexpr int TILE = 64;
constexpr int TPP = SK / TILE;
constexpr int IPP = 64;
constexpr int SPL = IPP / 32;
constexpr int TPI = TPP / IPP;
constexpr int N_A = NPAIR * IPP;
constexpr int N_Q = NQC / 32;
constexpr int N_G = FF / 32;
constexpr int NCB = DM / 64;
constexpr int N_DR = FF / 256;
constexpr int N_D = N_DR * NCB;
constexpr int N_O = HKV * NCB;
constexpr int N_TOTAL = N_A + N_G + N_D + N_O;
constexpr int NFIN = HKV + N_DR;
constexpr int NBLK = NCB * 4;
constexpr int NFTASK = NBLK * 16;

constexpr int NSLOTS = 4;
constexpr int CAP = 2;
constexpr uint32_t PACE = 2500;
constexpr int LAG = 8;
constexpr int PRING = 16;
static_assert(IPP == 64, "taper table / arrival masks are written for 64 splits");
static_assert((NPAIR / PRING) % 2 == 0 && PRING > LAG, "ring tag parity / reuse distance");
constexpr int NTAILP = 128 / IPP;
constexpr int NG2 = 56;
constexpr int NG1 = N_G - NG2;
constexpr int NLATE = 4;
constexpr int SLOT_BYTES = 36864;
constexpr int NTHREADS = 320;

enum : uint32_t { T_A = 0, T_Q = 1, T_GATE = 2, T_UP = 3, T_D = 4, T_O = 5, T_END = 6 };
constexpr uint32_t F_FIRST = 1u << 24, F_LAST = 1u << 25;
constexpr uint32_t C_END = 0xffffffffu;

constexpr int SM_XN = NSLOTS * SLOT_BYTES;
constexpr int SM_CBUF = SM_XN + 9216;
constexpr int SM_CML = SM_CBUF + 2 * 4 * 1024;
constexpr int SM_RED = SM_CML + 128;
constexpr int SM_BAR = SM_RED + 1024;
constexpr int SM_MISC = SM_BAR + 4 * NSLOTS * 8;
constexpr int SM_TOTAL = SM_MISC + 128;
constexpr int SMEM_BYTES = SM_TOTAL + 1024;

struct alignas(128) Ctr { uint32_t v; uint32_t pad[31]; };
__device__ Ctr g_epoch, g_work;
__device__ Ctr g_qmask[HKV], g_pmask[NPAIR], g_omask[NPAIR], g_hmask[N_DR], g_fmask[NBLK];
__device__ alignas(128) uint32_t g_q[NPAIR * 256];
__device__ alignas(128) uint32_t g_po[PRING * IPP * DH * 2];
__device__ alignas(128) uint32_t g_pml[PRING * IPP * 8];
__device__ alignas(128) uint32_t g_o[NB * NQC];
__device__ alignas(128) uint32_t g_h[NB * FF];
__device__ alignas(128) uint32_t g_fin[NFTASK * NFIN * 8];

#define SPIN_GUARD(it, lim) do { if (++(it) > (lim)) __trap(); } while (0)
__device__ __forceinline__ uint32_t smem_u32(const void* p) { return (uint32_t)__cvta_generic_to_shared(p); }
__device__ __forceinline__ void mbar_init(uint32_t bar, uint32_t cnt) {
    asm volatile("mbarrier.init.shared::cta.b64 [%0], %1;" ::"r"(bar), "r"(cnt) : "memory");
}
__device__ __forceinline__ void mbar_arrive(uint32_t bar) {
    asm volatile("mbarrier.arrive.shared::cta.b64 _, [%0];" ::"r"(bar) : "memory");
}
__device__ __forceinline__ void mbar_arrive_expect_tx(uint32_t bar, uint32_t bytes) {
    asm volatile("mbarrier.arrive.expect_tx.shared::cta.b64 _, [%0], %1;" ::"r"(bar), "r"(bytes) : "memory");
}
__device__ __forceinline__ bool mbar_try_wait(uint32_t bar, uint32_t parity) {
    uint32_t ok;
    asm volatile("{\n.reg .pred p;\nmbarrier.try_wait.parity.shared::cta.b64 p, [%1], %2;\nselp.u32 %0, 1, 0, p;\n}"
                 : "=r"(ok) : "r"(bar), "r"(parity) : "memory");
    return ok != 0;
}
__device__ __forceinline__ bool mbar_test_wait(uint32_t bar, uint32_t parity) {
    uint32_t ok;
    asm volatile("{\n.reg .pred p;\nmbarrier.test_wait.parity.shared::cta.b64 p, [%1], %2;\nselp.u32 %0, 1, 0, p;\n}"
                 : "=r"(ok) : "r"(bar), "r"(parity) : "memory");
    return ok != 0;
}
__device__ __forceinline__ void mbar_wait(uint32_t bar, uint32_t parity) {
    uint32_t it = 0;
    while (!mbar_try_wait(bar, parity)) SPIN_GUARD(it, 1u << 20);
}
__device__ __forceinline__ uint32_t ld_relaxed(const uint32_t* p) {
    uint32_t v;
    asm volatile("ld.relaxed.gpu.global.u32 %0, [%1];" : "=r"(v) : "l"(p) : "memory");
    return v;
}
__device__ __forceinline__ uint2 ld_relaxed2(const uint32_t* p) {
    uint2 v;
    asm volatile("ld.relaxed.gpu.global.v2.u32 {%0,%1}, [%2];" : "=r"(v.x), "=r"(v.y) : "l"(p) : "memory");
    return v;
}
__device__ __forceinline__ uint4 ld_relaxed4(const uint32_t* p) {
    uint4 v;
    asm volatile("ld.relaxed.gpu.global.v4.u32 {%0,%1,%2,%3}, [%4];" : "=r"(v.x), "=r"(v.y), "=r"(v.z), "=r"(v.w) : "l"(p) : "memory");
    return v;
}
__device__ __forceinline__ void st_relaxed(uint32_t* p, uint32_t v) {
    asm volatile("st.relaxed.gpu.global.u32 [%0], %1;" ::"l"(p), "r"(v) : "memory");
}
__device__ __forceinline__ void st_relaxed2(uint32_t* p, uint32_t a, uint32_t b) {
    asm volatile("st.relaxed.gpu.global.v2.u32 [%0], {%1,%2};" ::"l"(p), "r"(a), "r"(b) : "memory");
}
__device__ __forceinline__ void st_relaxed4(uint32_t* p, uint32_t a, uint32_t b, uint32_t c, uint32_t d) {
    asm volatile("st.relaxed.gpu.global.v4.u32 [%0], {%1,%2,%3,%4};" ::"l"(p), "r"(a), "r"(b), "r"(c), "r"(d) : "memory");
}
__device__ __forceinline__ void red_xor(uint32_t* p, uint32_t bits) {
    asm volatile("red.relaxed.gpu.global.xor.b32 [%0], %1;" ::"l"(p), "r"(bits) : "memory");
}
__device__ __forceinline__ uint32_t tag_f32(float v, uint32_t tag) { return (__float_as_uint(v) & ~1u) | tag; }
__device__ __forceinline__ uint32_t tag_bf16(float v, uint32_t tag) {
    return ((uint32_t)__bfloat16_as_ushort(__float2bfloat16_rn(v)) << 16) | tag;
}
__device__ __forceinline__ uint32_t ring_tag(uint32_t pair) { return ((pair / PRING) & 1u) ^ 1u; }
__device__ __forceinline__ float untag(uint32_t w) { return __uint_as_float(w & ~1u); }
__device__ __forceinline__ uint32_t mis4(uint4 v, uint32_t tag) { return (v.x ^ tag) | (v.y ^ tag) | (v.z ^ tag) | (v.w ^ tag); }
__device__ __forceinline__ uint32_t hi16x2(uint32_t lo, uint32_t hi) { return __byte_perm(lo, hi, 0x7632); }
__device__ __forceinline__ uint4 pack8(uint4 a, uint4 b) {
    return make_uint4(hi16x2(a.x, a.y), hi16x2(a.z, a.w), hi16x2(b.x, b.y), hi16x2(b.z, b.w));
}
__device__ __forceinline__ uint4 poll_bf16x8(const uint32_t* p, uint32_t tag) {
    uint32_t it = 0;
    while (true) {
        const uint4 a = ld_relaxed4(p), b = ld_relaxed4(p + 4);
        if (!((mis4(a, tag) | mis4(b, tag)) & 1u)) return pack8(a, b);
        SPIN_GUARD(it, 1u << 22);
    }
}
__device__ __forceinline__ void tma_2d(uint32_t dst, const CUtensorMap* map, int c0, int c1, uint32_t bar, uint64_t pol) {
    asm volatile("cp.async.bulk.tensor.2d.shared::cluster.global.mbarrier::complete_tx::bytes.L2::cache_hint "
                 "[%0], [%1, {%3, %4}], [%2], %5;"
                 ::"r"(dst), "l"(map), "r"(bar), "r"(c0), "r"(c1), "l"(pol) : "memory");
}
__device__ __forceinline__ void tma_2d_nohint(uint32_t dst, const CUtensorMap* map, int c0, int c1, uint32_t bar) {
    asm volatile("cp.async.bulk.tensor.2d.shared::cluster.global.mbarrier::complete_tx::bytes "
                 "[%0], [%1, {%3, %4}], [%2];"
                 ::"r"(dst), "l"(map), "r"(bar), "r"(c0), "r"(c1) : "memory");
}
__device__ __forceinline__ void tma_3d(uint32_t dst, const CUtensorMap* map, int c0, int c1, int c2, uint32_t bar, uint64_t pol) {
    asm volatile("cp.async.bulk.tensor.3d.shared::cluster.global.mbarrier::complete_tx::bytes.L2::cache_hint "
                 "[%0], [%1, {%3, %4, %5}], [%2], %6;"
                 ::"r"(dst), "l"(map), "r"(bar), "r"(c0), "r"(c1), "r"(c2), "l"(pol) : "memory");
}
__device__ __forceinline__ void ldsm_x4(uint32_t addr, uint32_t& r0, uint32_t& r1, uint32_t& r2, uint32_t& r3) {
    asm volatile("ldmatrix.sync.aligned.m8n8.x4.shared.b16 {%0,%1,%2,%3}, [%4];"
                 : "=r"(r0), "=r"(r1), "=r"(r2), "=r"(r3) : "r"(addr) : "memory");
}
__device__ __forceinline__ void ldsm_x4_t(uint32_t addr, uint32_t& r0, uint32_t& r1, uint32_t& r2, uint32_t& r3) {
    asm volatile("ldmatrix.sync.aligned.m8n8.x4.trans.shared.b16 {%0,%1,%2,%3}, [%4];"
                 : "=r"(r0), "=r"(r1), "=r"(r2), "=r"(r3) : "r"(addr) : "memory");
}
__device__ __forceinline__ void mma_bf16(float (&d)[4], uint32_t a0, uint32_t a1, uint32_t a2, uint32_t a3, uint32_t b0, uint32_t b1) {
    asm volatile("mma.sync.aligned.m16n8k16.row.col.f32.bf16.bf16.f32 {%0,%1,%2,%3}, {%4,%5,%6,%7}, {%8,%9}, {%0,%1,%2,%3};"
                 : "+f"(d[0]), "+f"(d[1]), "+f"(d[2]), "+f"(d[3])
                 : "r"(a0), "r"(a1), "r"(a2), "r"(a3), "r"(b0), "r"(b1));
}
__device__ __forceinline__ uint4 lds128(uint32_t addr) {
    uint4 v;
    asm volatile("ld.shared.v4.u32 {%0,%1,%2,%3}, [%4];" : "=r"(v.x), "=r"(v.y), "=r"(v.z), "=r"(v.w) : "r"(addr) : "memory");
    return v;
}
__device__ __forceinline__ void sts128(uint32_t addr, uint4 v) {
    asm volatile("st.shared.v4.u32 [%0], {%1,%2,%3,%4};" ::"r"(addr), "r"(v.x), "r"(v.y), "r"(v.z), "r"(v.w) : "memory");
}
__device__ __forceinline__ void named_bar_sync(int id, int n) { asm volatile("bar.sync %0, %1;" ::"r"(id), "r"(n) : "memory"); }
__device__ __forceinline__ void named_bar_arrive(int id, int n) { asm volatile("bar.arrive %0, %1;" ::"r"(id), "r"(n) : "memory"); }
__device__ __forceinline__ float ex2(float x) { float y; asm("ex2.approx.ftz.f32 %0, %1;" : "=f"(y) : "f"(x)); return y; }
__device__ __forceinline__ float warp_max(float x) {
    int i = __float_as_int(x);
    i ^= (i >> 31) & 0x7fffffff;
    i = __reduce_max_sync(0xffffffffu, i);
    i ^= (i >> 31) & 0x7fffffff;
    return __int_as_float(i);
}
template <int H, int X, int N>
__device__ __forceinline__ void fold(float (&v)[N], int lane) {
    const bool up = lane & X;
#pragma unroll
    for (int i = 0; i < H; i++) {
        const float lo = v[i], hi = v[i + H];
        const float keep = up ? hi : lo, send = up ? lo : hi;
        v[i] = keep + __shfl_xor_sync(0xffffffffu, send, X);
    }
}
__device__ __forceinline__ float rbf(float x) { return __bfloat162float(__float2bfloat16_rn(x)); }
__device__ __forceinline__ uint32_t pack_bf16(float lo, float hi) {
    __nv_bfloat162 v = __floats2bfloat162_rn(lo, hi);
    return *reinterpret_cast<uint32_t*>(&v);
}
__device__ __forceinline__ float bf_lo(uint32_t p) { return __uint_as_float(p << 16); }
__device__ __forceinline__ float bf_hi(uint32_t p) { return __uint_as_float(p & 0xffff0000u); }
__device__ __forceinline__ int bfrag_idx(int batch, int k) {
    int r = k & 31;
    return (k >> 5) * 256 + (batch * 4 + ((r & 7) >> 1)) * 8 + ((r >> 3) << 1) + (r & 1);
}

__global__ void __launch_bounds__(NTHREADS, 1)
fused_decode_kernel(const __grid_constant__ CUtensorMap mapK, const __grid_constant__ CUtensorMap mapV,
                    const __grid_constant__ CUtensorMap mapWq, const __grid_constant__ CUtensorMap mapWg,
                    const __grid_constant__ CUtensorMap mapWu, const __grid_constant__ CUtensorMap mapWd,
                    const __grid_constant__ CUtensorMap mapWo,
                    const __nv_bfloat16* __restrict__ x, __nv_bfloat16* __restrict__ out,
                    const char* __restrict__ wq_raw) {
    extern __shared__ unsigned char smem_raw[];
    if (threadIdx.x == 288 && blockIdx.x < 128) {
        asm volatile("cp.async.bulk.prefetch.L2.global [%0], %1;" ::"l"(wq_raw + (size_t)blockIdx.x * 36864u), "r"(36864u) : "memory");
    }
    const uint32_t sbase = (smem_u32(smem_raw) + 1023u) & ~1023u;
    unsigned char* sptr = smem_raw + (sbase - smem_u32(smem_raw));
    const int tid = threadIdx.x, warp = tid >> 5, lane = tid & 31;
    const uint32_t bar_full = sbase + SM_BAR;
    const uint32_t bar_empty = bar_full + NSLOTS * 8;
    const uint32_t bar_qreq = bar_empty + NSLOTS * 8;
    const uint32_t bar_qfull = bar_qreq + NSLOTS * 8;
    volatile uint32_t* s_meta = reinterpret_cast<volatile uint32_t*>(sptr + SM_MISC);
    volatile uint32_t* s_qreq = reinterpret_cast<volatile uint32_t*>(sptr + SM_MISC + 32);
    volatile uint32_t* s_misc = reinterpret_cast<volatile uint32_t*>(sptr + SM_MISC + 64);
    uint32_t epoch;
    uint32_t npre = 0;
    if (tid == 256) {
#pragma unroll
        for (int i = 0; i < NSLOTS; i++) mbar_init(bar_full + i * 8, 1);
        asm volatile("fence.mbarrier_init.release.cluster;" ::: "memory");
        asm volatile("fence.proxy.async.shared::cta;" ::: "memory");
        const int col = blockIdx.x * 32;
#pragma unroll
        for (int i = 0; i < 3; i++) {
            if (blockIdx.x < (i == 0 ? N_Q : NG1)) {
                const CUtensorMap* map = i == 0 ? &mapWq : i == 1 ? &mapWg : &mapWu;
                const uint32_t dst = sbase + npre * SLOT_BYTES, bar = bar_full + npre * 8;
                s_meta[npre] = ((i == 0 ? T_Q : i == 1 ? T_GATE : T_UP) << 28) | blockIdx.x;
                mbar_arrive_expect_tx(bar, 576 * 64);
                tma_2d_nohint(dst, map, col, 0, bar);
                tma_2d_nohint(dst + 192 * 64, map, col, 192, bar);
                tma_2d_nohint(dst + 384 * 64, map, col, 384, bar);
                npre++;
            }
        }
    }

    if (warp == 8) {
        if (lane == 0) {
#pragma unroll
            for (int i = 0; i < NSLOTS; i++) {
                mbar_init(bar_empty + i * 8, 4); mbar_init(bar_qreq + i * 8, 1); mbar_init(bar_qfull + i * 8, 1);
            }
            s_misc[1] = 0;
        }
        __syncwarp();
        named_bar_arrive(1, NTHREADS);
        epoch = ld_relaxed(&g_epoch.v);
        if (lane == 0) {
            uint64_t pol_stream, pol_norm;
            asm volatile("createpolicy.fractional.L2::evict_first.b64 %0, 1.0;" : "=l"(pol_stream));
            asm volatile("createpolicy.fractional.L2::evict_normal.b64 %0, 1.0;" : "=l"(pol_norm));

            static_assert(NSLOTS > 3, "prologue fills up to three slots");
            uint32_t slot = npre, phase = 1;
            uint32_t lslot = 0, lphase = 0;
            uint32_t inflight = npre, nq = 0;
            auto wait_free = [&]() { mbar_wait(bar_empty + slot * 8, phase); };
            auto throttle = [&](uint32_t cap) {
                while (inflight >= cap) {
                    mbar_wait(bar_full + lslot * 8, lphase);
                    if (++lslot == NSLOTS) { lslot = 0; lphase ^= 1; }
                    inflight--;
                }
            };
            long long t_issue = 0;
            uint32_t gap_now = 0x7fffffff;
            auto pace = [&](uint32_t gap) {
                throttle(2);
                uint32_t it = 0;
                while (inflight >= 1 && clock64() - t_issue < (long long)gap) {
                    if (mbar_test_wait(bar_full + lslot * 8, lphase)) {
                        if (++lslot == NSLOTS) { lslot = 0; lphase ^= 1; }
                        inflight--;
                    }
                    SPIN_GUARD(it, 1u << 24);
                }
                t_issue = clock64();
            };
            auto advance = [&]() { inflight++; if (++slot == NSLOTS) { slot = 0; phase ^= 1; } };
            auto post_stage = [&](uint32_t req) {
                s_qreq[nq] = req | (slot << 16);
                mbar_arrive(bar_qreq + nq * 8);
                if (++nq == NSLOTS) nq = 0;
            };
            auto issue_x = [&](const CUtensorMap* map, uint32_t meta, int col, uint32_t cap) {
                wait_free();
                if (cap) throttle(cap); else pace(gap_now);
                const uint32_t dst = sbase + slot * SLOT_BYTES, bar = bar_full + slot * 8;
                s_meta[slot] = meta;
                mbar_arrive_expect_tx(bar, 576 * 64);
                tma_2d(dst, map, col, 0, bar, pol_norm);
                tma_2d(dst + 192 * 64, map, col, 192, bar, pol_norm);
                tma_2d(dst + 384 * 64, map, col, 384, bar, pol_norm);
                advance();
            };
            auto issue_y = [&](const CUtensorMap* map, uint32_t type, uint32_t i) {
                wait_free();
                post_stage((type << 28) | (i / NCB));
                pace(gap_now);
                const uint32_t dst = sbase + slot * SLOT_BYTES, bar = bar_full + slot * 8;
                s_meta[slot] = (type << 28) | i;
                mbar_arrive_expect_tx(bar, 256 * 128);
                tma_2d(dst, map, (i % NCB) * 64, (i / NCB) * 256, bar, pol_stream);
                advance();
            };

            for (int qi = blockIdx.x + gridDim.x; qi < N_Q; qi += gridDim.x) issue_x(&mapWq, (T_Q << 28) | qi, qi * 32, CAP);

            auto claimed = [&](uint32_t ticket) {
                uint32_t e;
                asm volatile("mov.u32 %0, %1;" : "=r"(e) : "r"(epoch));
                return ticket - (e * (uint32_t)N_TOTAL - gridDim.x);
            };
            uint32_t item = blockIdx.x;
            if (item < (uint32_t)NG1) item = claimed(atomicAdd(&g_work.v, 1u));
            while (item < (uint32_t)N_TOTAL) {
                uint32_t next = 0;
                if (item - NG1 < (uint32_t)N_A) {
                    uint32_t ai = item - NG1;
                    int pair, tile0, tstep, ntile;
                    if (ai < (uint32_t)(N_A - NTAILP * IPP)) {
                        pair = ai / IPP; tile0 = ai % IPP; tstep = IPP; ntile = TPI;
                    } else {
                        const int r = ai - (N_A - NTAILP * IPP), c = r / NTAILP;
                        pair = NPAIR - NTAILP + r % NTAILP;
                        ntile = c < 16 ? 3 : c < 48 ? 2 : 1;
                        tile0 = c < 16 ? 3 * c : c < 48 ? 16 + 2 * c : 64 + c;
                        tstep = 1;
                        ai = pair * IPP + c;
                    }
                    s_misc[1] = pair;
#pragma unroll 1
                    for (int j = 0; j < ntile; j++) {
                        wait_free();
                        if (j == 0) post_stage((T_A << 28) | pair);
                        throttle(CAP);
                        const uint32_t dst = sbase + slot * SLOT_BYTES, bar = bar_full + slot * 8;
                        s_meta[slot] = (T_A << 28) | (j == 0 ? F_FIRST : 0u) | (j == ntile - 1 ? F_LAST : 0u) | ai;
                        mbar_arrive_expect_tx(bar, 2 * TILE * 256);
                        const int row = pair * SK + (tile0 + j * tstep) * TILE;
                        tma_3d(dst, &mapK, 0, row, 0, bar, pol_stream);
                        tma_3d(dst + TILE * 256, &mapV, 0, row, 0, bar, pol_stream);
                        if (j == ntile - 1) next = atomicAdd(&g_work.v, 1u);
                        advance();
                    }
                } else if (item < (uint32_t)NG1) {
                    next = atomicAdd(&g_work.v, 1u);
                    issue_x(&mapWg, (T_GATE << 28) | item, item * 32, CAP);
                    issue_x(&mapWu, (T_UP << 28) | item, item * 32, CAP);
                } else {
                    s_misc[1] = NPAIR;
                    if (t_issue == 0) t_issue = clock64();
                    constexpr uint32_t ND1 = (NG1 / 8) * NCB, NO1 = (HKV - NLATE) * NCB;
                    uint32_t i = item - N_A;
                    if (i < (uint32_t)N_G) {
                        issue_x(&mapWg, (T_GATE << 28) | i, i * 32, 0);
                        gap_now = PACE;
                        issue_x(&mapWu, (T_UP << 28) | i, i * 32, 0);
                    } else if ((i -= N_G) < ND1) issue_y(&mapWd, T_D, i);
                    else if (i < ND1 + NO1) issue_y(&mapWo, T_O, i - ND1);
                    else if (i < N_D + NO1) issue_y(&mapWd, T_D, i - NO1);
                    else issue_y(&mapWo, T_O, i - N_D);
                    next = atomicAdd(&g_work.v, 1u);
                    gap_now = PACE;
                }
                item = claimed(next);
            }
            s_misc[1] = NPAIR;
            wait_free();
            s_qreq[nq] = C_END;
            mbar_arrive(bar_qreq + nq * 8);
            s_meta[slot] = T_END << 28;
            mbar_arrive(bar_full + slot * 8);
        }
        __syncwarp();
    } else {
        if (warp < 8) {
            const __nv_bfloat162* xr = reinterpret_cast<const __nv_bfloat162*>(x + warp * DM);
            float2 v[9];
#pragma unroll
            for (int i = 0; i < 9; i++) v[i] = __bfloat1622float2(xr[lane + 32 * i]);
            float s = 0.f;
#pragma unroll
            for (int i = 0; i < 9; i++) s += v[i].x + v[i].y;
#pragma unroll
            for (int o = 16; o; o >>= 1) s += __shfl_xor_sync(0xffffffffu, s, o);
            const float mean = s * (1.0f / DM);
            float q = 0.f;
#pragma unroll
            for (int i = 0; i < 9; i++) { float a = v[i].x - mean, b = v[i].y - mean; q += a * a + b * b; }
#pragma unroll
            for (int o = 16; o; o >>= 1) q += __shfl_xor_sync(0xffffffffu, q, o);
            const float mb = rbf(mean);
            const float sd = rbf(sqrtf(rbf(rbf(q * (1.0f / DM)) + 1e-5f)));
            __nv_bfloat16* xn = reinterpret_cast<__nv_bfloat16*>(sptr + SM_XN);
#pragma unroll
            for (int i = 0; i < 9; i++) {
                const int k = 2 * (lane + 32 * i);
                const uint32_t p = pack_bf16(rbf(v[i].x - mb) / sd, rbf(v[i].y - mb) / sd);
                *reinterpret_cast<uint32_t*>(xn + bfrag_idx(warp, k)) = p;
            }
        } else if (lane == 0) {
            s_misc[0] = ld_relaxed(&g_epoch.v);
        }
        named_bar_sync(1, NTHREADS);
        epoch = s_misc[0];
    }
    const uint32_t tag = (epoch & 1u) ^ 1u;
    const uint32_t mflip = tag - 1u;

    if (warp < 4) {
        constexpr float SCALE = 0.08838834764831845f, LOG2E = 1.4426950408889634f;
        uint32_t qa[16];
        float acc[8][4];
        float m_run = -INFINITY, l_run = 0.f;
        float gate[4] = {0.f, 0.f, 0.f, 0.f};
        uint32_t slot = 0, phase = 0, nitem = 0, qphase = 0;
        const int li = lane >> 3, lr = lane & 7;
        const uint32_t k_off = (uint32_t)((warp * 16 + lr) * 128);
        const uint32_t v_off = (uint32_t)((warp * 16 + (li >> 1) * 8 + lr) * 128);
#pragma unroll
        for (int i = 0; i < 16; i++) qa[i] = 0;
#pragma unroll
        for (int i = 0; i < 8; i++) { acc[i][0] = acc[i][1] = acc[i][2] = acc[i][3] = 0.f; }

        while (true) {
            mbar_wait(bar_full + slot * 8, phase);
            const uint32_t sb = sbase + slot * SLOT_BYTES;
            const uint32_t meta = s_meta[slot];
            const uint32_t type = meta >> 28;
            if (type == T_A) {
                if (meta & F_FIRST) {
                    mbar_wait(bar_qfull + slot * 8, (qphase >> slot) & 1u);
                    qphase ^= 1u << slot;
                    if (lane < 8) {
#pragma unroll
                        for (int i = 0; i < 4; i++) {
                            uint4 t = lds128(sb + 2 * TILE * 256 + lane * 64 + i * 16);
                            qa[4 * i] = t.x; qa[4 * i + 1] = t.y; qa[4 * i + 2] = t.z; qa[4 * i + 3] = t.w;
                        }
                    }
                    __syncwarp();
                    m_run = -INFINITY; l_run = 0.f;
#pragma unroll
                    for (int i = 0; i < 8; i++) { acc[i][0] = acc[i][1] = acc[i][2] = acc[i][3] = 0.f; }
                }
                float s[4][4];
#pragma unroll
                for (int i = 0; i < 4; i++) { s[i][0] = s[i][1] = s[i][2] = s[i][3] = 0.f; }
#pragma unroll
                for (int half = 0; half < 2; half++)
#pragma unroll
                    for (int cc = 0; cc < 2; cc++)
#pragma unroll
                        for (int nt = 0; nt < 2; nt++) {
                            uint32_t r0, r1, r2, r3;
                            ldsm_x4(sb + half * 8192 + k_off + nt * 1024 + (((cc * 4 + li) ^ lr) << 4), r0, r1, r2, r3);
                            const int ks = half * 4 + cc * 2;
                            mma_bf16(s[nt * 2 + 0], qa[2 * ks], 0u, qa[2 * ks + 1], 0u, r0, r1);
                            mma_bf16(s[nt * 2 + 1], qa[2 * ks + 2], 0u, qa[2 * ks + 3], 0u, r2, r3);
                        }
                uint32_t va[8][4];
#pragma unroll
                for (int mt = 0; mt < 8; mt++)
                    ldsm_x4_t(sb + TILE * 256 + (mt >> 2) * 8192 + v_off + (((((mt & 3) << 1) + (li & 1)) ^ lr) << 4),
                              va[mt][0], va[mt][1], va[mt][2], va[mt][3]);
                __syncwarp();
                if (lane == 0) mbar_arrive(bar_empty + slot * 8);

                const uint32_t r01 = pack_bf16(s[0][0] + s[1][0], s[0][1] + s[1][1]), r23 = pack_bf16(s[2][0] + s[3][0], s[2][1] + s[3][1]);
                const uint32_t t01 = pack_bf16(bf_lo(r01) * SCALE, bf_hi(r01) * SCALE), t23 = pack_bf16(bf_lo(r23) * SCALE, bf_hi(r23) * SCALE);
                const float s0 = bf_lo(t01) * LOG2E, s1 = bf_hi(t01) * LOG2E, s2 = bf_lo(t23) * LOG2E, s3 = bf_hi(t23) * LOG2E;
                float mx = fmaxf(fmaxf(s0, s1), fmaxf(s2, s3));
                mx = fmaxf(mx, __shfl_xor_sync(0xffffffffu, mx, 1));
                mx = fmaxf(mx, __shfl_xor_sync(0xffffffffu, mx, 2));
                const float m_new = fmaxf(m_run, mx);
                const float alpha = ex2(m_run - m_new);
                m_run = m_new;
                const uint32_t b0 = pack_bf16(ex2(s0 - m_new), ex2(s1 - m_new));
                const uint32_t b1 = pack_bf16(ex2(s2 - m_new), ex2(s3 - m_new));
                const float psum = (bf_lo(b0) + bf_hi(b0)) + (bf_lo(b1) + bf_hi(b1));
                l_run = l_run * alpha + psum;
                const float a0 = __shfl_sync(0xffffffffu, alpha, 0), a1 = __shfl_sync(0xffffffffu, alpha, 4);
                if (a0 != 1.0f || a1 != 1.0f) {
#pragma unroll
                    for (int mt = 0; mt < 8; mt++) { acc[mt][0] *= a0; acc[mt][1] *= a1; acc[mt][2] *= a0; acc[mt][3] *= a1; }
                }
#pragma unroll
                for (int mt = 0; mt < 8; mt++) mma_bf16(acc[mt], va[mt][0], va[mt][1], va[mt][2], va[mt][3], b0, b1);

                if (meta & F_LAST) {
                    const uint32_t buf = nitem & 1;
                    float l = l_run;
                    l += __shfl_xor_sync(0xffffffffu, l, 1);
                    l += __shfl_xor_sync(0xffffffffu, l, 2);
                    float2* cb = reinterpret_cast<float2*>(sptr + SM_CBUF + buf * 4096);
                    float* cml = reinterpret_cast<float*>(sptr + SM_CML + buf * 64);
                    if ((lane & 3) == 0) {
#pragma unroll
                        for (int mt = 0; mt < 8; mt++) {
                            cb[warp * 128 + mt * 16 + (lane >> 2)] = make_float2(acc[mt][0], acc[mt][1]);
                            cb[warp * 128 + mt * 16 + 8 + (lane >> 2)] = make_float2(acc[mt][2], acc[mt][3]);
                        }
                        if (lane < 8) { cml[warp * 4 + (lane >> 2)] = m_run; cml[warp * 4 + 2 + (lane >> 2)] = l; }
                    }
                    const uint32_t item = meta & 0xffffffu, pair = item / IPP, split = item % IPP;
                    named_bar_sync(2, 128);
                    float4 ml[4];
                    float2 ov[4];
#pragma unroll
                    for (int w = 0; w < 4; w++) { ml[w] = reinterpret_cast<const float4*>(cml)[w]; ov[w] = cb[w * 128 + tid]; }
                    const float M0 = fmaxf(fmaxf(ml[0].x, ml[1].x), fmaxf(ml[2].x, ml[3].x));
                    const float M1 = fmaxf(fmaxf(ml[0].y, ml[1].y), fmaxf(ml[2].y, ml[3].y));
                    float o0 = 0.f, o1 = 0.f, L0 = 0.f, L1 = 0.f;
#pragma unroll
                    for (int w = 0; w < 4; w++) {
                        const float e0 = ex2(ml[w].x - M0), e1 = ex2(ml[w].y - M1);
                        o0 += e0 * ov[w].x; o1 += e1 * ov[w].y;
                        L0 += e0 * ml[w].z; L1 += e1 * ml[w].w;
                    }
                    const int pos = (tid & ~31) + ((tid & 7) >> 1) * 8 + ((tid >> 3) & 3) * 2 + (tid & 1);
                    const uint32_t pr = pair % PRING, pt = ring_tag(pair);
                    st_relaxed2(g_po + ((pr * 32 + (pos >> 2)) * IPP + split) * 8 + (pos & 3) * 2, tag_f32(o0, pt), tag_f32(o1, pt));
                    if (tid < 2) {
                        const uint32_t u0 = __float_as_uint(M0), u1 = __float_as_uint(M1);
                        st_relaxed4(g_pml + (pr * IPP + split) * 8 + tid * 4, tid ? tag_f32(L0, pt) : (u0 << 16) | pt, tid ? tag_f32(L1, pt) : (u0 & 0xffff0000u) | pt,
                                    (u1 << 16) | pt, (u1 & 0xffff0000u) | pt);
                        if (tid == 0) red_xor(&g_pmask[pair].v + (split >> 5), 1u << (split & 31));
                    }
                    nitem++;
                }
            } else {
                if (type <= T_UP) {
                    const int kh = warp >> 1, mt = warp & 1;
                    float c0[4] = {0.f, 0.f, 0.f, 0.f}, c1[4] = {0.f, 0.f, 0.f, 0.f};
                    const int row0 = kh * 288 + (li >> 1) * 8 + lr;
                    const uint32_t a_addr = sb + row0 * 64 + ((((mt << 1) + (li & 1)) ^ ((row0 >> 1) & 3)) << 4);
                    const uint32_t b_addr = sbase + SM_XN + kh * 9 * 512 + lane * 16;
#pragma unroll
                    for (int kb = 0; kb < 9; kb++) {
                        const uint4 b = lds128(b_addr + kb * 512);
                        uint32_t r0, r1, r2, r3;
                        ldsm_x4_t(a_addr + kb * 2048, r0, r1, r2, r3);
                        mma_bf16(c0, r0, r1, r2, r3, b.x, b.y);
                        ldsm_x4_t(a_addr + kb * 2048 + 1024, r0, r1, r2, r3);
                        mma_bf16(c1, r0, r1, r2, r3, b.z, b.w);
                    }
                    __syncwarp();
                    if (lane == 0) mbar_arrive(bar_empty + slot * 8);
#pragma unroll
                    for (int i = 0; i < 4; i++) c0[i] += c1[i];
                    float4* red = reinterpret_cast<float4*>(sptr + SM_RED) + mt * 32 + lane;
                    if (kh == 1) *red = make_float4(c0[0], c0[1], c0[2], c0[3]);
                    named_bar_sync(2, 128);
                    if (kh == 0) {
                        const float4 o = *red;
                        c0[0] += o.x; c0[1] += o.y; c0[2] += o.z; c0[3] += o.w;
                        const uint32_t idx = meta & 0xffffffu;
                        const int col = idx * 32 + mt * 16 + (lane >> 2), bt = (lane & 3) * 2;
                        if (type == T_Q) {
#pragma unroll
                            for (int i = 0; i < 4; i++) {
                                const int n = col + (i >> 1) * 8, b = bt + (i & 1);
                                const int head = n >> 7, d = n & 127, r = d & 15;
                                const int off = (((head & 1) * 4 + ((r & 7) >> 1)) * 8 + (d >> 4)) * 4 + ((r >> 3) << 1) + (r & 1);
                                st_relaxed(g_q + (b * HKV + (head >> 1)) * 256 + off, tag_bf16(c0[i], tag));
                            }
                            if (lane == 0) red_xor(&g_qmask[idx >> 3].v, 1u << ((idx & 7) * 2 + mt));
                        } else if (type == T_GATE) {
#pragma unroll
                            for (int i = 0; i < 4; i++) gate[i] = c0[i];
                        } else {
#pragma unroll
                            for (int i = 0; i < 4; i++) {
                                const float g = rbf(gate[i]);
                                const float ge = rbf(0.5f * g * (1.0f + tanhf(0.7978845608028654f * (g + 0.044715f * g * g * g))));
                                st_relaxed(g_h + bfrag_idx(bt + (i & 1), col + (i >> 1) * 8), tag_bf16(ge * rbf(c0[i]), tag));
                            }
                            if (lane == 0) red_xor(&g_hmask[idx >> 3].v, 1u << ((idx & 7) * 2 + mt));
                        }
                    }
                    named_bar_sync(2, 128);
                } else if (type <= T_O) {
                    const uint32_t idx = meta & 0xffffffu;
                    const int rb = idx / NCB, blk = (idx % NCB) * 4 + warp;
                    const int part = type == T_O ? rb : HKV + rb;
                    const uint32_t a_addr = sb + ((li >> 1) * 8 + lr) * 128 + ((((warp << 1) + (li & 1)) ^ lr) << 4);
                    uint32_t* dstp = g_fin + ((blk * 16 + (lane >> 1)) * NFIN + part) * 8 + (lane & 1) * 4;
                    uint32_t* mskp = &g_fmask[blk].v + (part >> 5);
                    uint32_t wa[16][4];
#pragma unroll
                    for (int ks = 0; ks < 16; ks++) ldsm_x4_t(a_addr + ks * 2048, wa[ks][0], wa[ks][1], wa[ks][2], wa[ks][3]);
                    mbar_wait(bar_qfull + slot * 8, (qphase >> slot) & 1u);
                    qphase ^= 1u << slot;
                    if (lane == 0) red_xor(mskp, 1u << (part & 31));
                    uint4 bf[8];
#pragma unroll
                    for (int kb = 0; kb < 8; kb++) bf[kb] = lds128(sb + 32768 + kb * 512 + lane * 16);
                    float c[4][4];
#pragma unroll
                    for (int i = 0; i < 4; i++) { c[i][0] = c[i][1] = c[i][2] = c[i][3] = 0.f; }
#pragma unroll
                    for (int kb = 0; kb < 8; kb++) {
                        mma_bf16(c[(kb & 1) * 2], wa[2 * kb][0], wa[2 * kb][1], wa[2 * kb][2], wa[2 * kb][3], bf[kb].x, bf[kb].y);
                        mma_bf16(c[(kb & 1) * 2 + 1], wa[2 * kb + 1][0], wa[2 * kb + 1][1], wa[2 * kb + 1][2], wa[2 * kb + 1][3], bf[kb].z, bf[kb].w);
                    }
                    st_relaxed4(dstp, tag_f32((c[0][0] + c[1][0]) + (c[2][0] + c[3][0]), tag), tag_f32((c[0][1] + c[1][1]) + (c[2][1] + c[3][1]), tag),
                                tag_f32((c[0][2] + c[1][2]) + (c[2][2] + c[3][2]), tag), tag_f32((c[0][3] + c[1][3]) + (c[2][3] + c[3][3]), tag));
                    __syncwarp();
                    if (lane == 0) mbar_arrive(bar_empty + slot * 8);
                } else {
                    break;
                }
            }
            if (++slot == NSLOTS) { slot = 0; phase ^= 1; }
        }
        return;
    }
    if (warp == 9) {
        uint32_t nq = 0, ph = 0, q_seen = 0;
        while (true) {
            mbar_wait(bar_qreq + nq * 8, ph);
            const uint32_t req = s_qreq[nq];
            if (req == C_END) break;
            const uint32_t type = req >> 28, slot = (req >> 16) & 0xffu, idx = req & 0xffffu;
            const uint32_t dst = sbase + slot * SLOT_BYTES + 32768;
            uint32_t it = 0;
            if (type == T_A) {
                const uint32_t g = idx % HKV;
                if (!((q_seen >> g) & 1u)) {
                    while (((ld_relaxed(&g_qmask[g].v) ^ mflip) & 0xffffu) != 0xffffu) { __nanosleep(100); SPIN_GUARD(it, 1u << 22); }
                    q_seen |= 1u << g;
                }
                uint32_t om = idx >= PRING ? ld_relaxed(&g_omask[idx - PRING].v) : ~mflip;
                sts128(dst + lane * 16, poll_bf16x8(g_q + idx * 256 + lane * 8, tag));
                while (((om ^ mflip) & 0xffffu) != 0xffffu) { __nanosleep(100); om = ld_relaxed(&g_omask[idx - PRING].v); SPIN_GUARD(it, 1u << 22); }
            } else {
                const int unit = (lane >> 2) * 32 + (lane & 3);
                const uint32_t* act = (type == T_O ? g_o : g_h) + idx * 2048 + unit * 8;
                const uint32_t d2 = dst + unit * 16;
                const bool late = type == T_O && idx >= HKV - NLATE;
                if (type == T_D && idx >= NG1 / 8)
                    while (((ld_relaxed(&g_hmask[idx].v) ^ mflip) & 0xffffu) != 0xffffu) { __nanosleep(50); SPIN_GUARD(it, 1u << 22); }
                uint4 a[16];
#pragma unroll
                for (int b = 0; b < 7; b++) { a[2 * b] = ld_relaxed4(act + b * 32); a[2 * b + 1] = ld_relaxed4(act + b * 32 + 4); }
                a[14] = a[15] = make_uint4(~tag, ~tag, ~tag, ~tag);
                if (!late) { a[14] = ld_relaxed4(act + 7 * 32); a[15] = ld_relaxed4(act + 7 * 32 + 4); }
                uint32_t pend = 0;
#pragma unroll
                for (int b = 0; b < 8; b++) {
                    pend |= ((mis4(a[2 * b], tag) | mis4(a[2 * b + 1], tag)) & 1u) << b;
                    sts128(d2 + b * 64, pack8(a[2 * b], a[2 * b + 1]));
                }
                if (late) {
                    const uint32_t* msk = &g_omask[(NB - 1) * HKV + idx].v;
                    uint32_t present = 0;
                    while (true) {
                        const uint32_t m = ld_relaxed(msk);
                        if ((pend & 0x80u) && present != 0) {
                            const uint4 u = ld_relaxed4(act + 7 * 32), w = ld_relaxed4(act + 7 * 32 + 4);
                            if (!((mis4(u, tag) | mis4(w, tag)) & 1u)) { sts128(d2 + 7 * 64, pack8(u, w)); pend &= 0x7fu; }
                        }
                        present = (m ^ mflip) & 0xffffu;
                        if (!__any_sync(0xffffffffu, pend & 0x80u)) break;
                        if (present == 0) __nanosleep(50);
                        SPIN_GUARD(it, 1u << 22);
                    }
                }
                while (pend) {
                    const int b = __ffs(pend) - 1;
                    pend &= pend - 1;
                    sts128(d2 + b * 64, poll_bf16x8(act + b * 32, tag));
                }
            }
            asm volatile("fence.proxy.async.shared::cta;" ::: "memory");
            __syncwarp();
            if (lane == 0) mbar_arrive(bar_qfull + slot * 8);
            if (++nq == NSLOTS) { nq = 0; ph ^= 1; }
        }
        return;
    }
    if (warp < 8) {
        for (int n = blockIdx.x; n < NPAIR * 4; n += gridDim.x) {
            const int pair = n >> 2, u = (n & 3) * 4 + (warp - 4);
            uint32_t it = 0;
            while ((int)s_misc[1] < min(pair + LAG, NPAIR)) {
                __nanosleep(300);
                SPIN_GUARD(it, 1u << 20);
            }
            const uint32_t* pml = g_pml + ((pair % PRING) * IPP + lane) * 8;
            const uint32_t* po = g_po + (((pair % PRING) * 32 + u * 2) * IPP + lane) * 8;
            const uint32_t pt = ring_tag(pair);
            uint32_t* dst = g_o + ((pair % HKV) * 8 + ((lane >> 1) & 1) * 4 + (u >> 2)) * 256 + ((pair / HKV) * 4 + (u & 3)) * 8 + (lane >> 2);
            uint4 pm[SPL], pv[SPL][4];
            uint2 pl[SPL];
            while (true) {
                const uint2 m = ld_relaxed2(&g_pmask[pair].v);
                const uint32_t lo = m.x ^ mflip, hi = SPL > 1 ? m.y ^ mflip : 0xffffffffu;
                if ((lo & hi) == 0xffffffffu) break;
                if (__popc(lo) < 16) __nanosleep(100);
                SPIN_GUARD(it, 1u << 22);
            }
            while (true) {
                uint32_t mis = 0;
#pragma unroll
                for (int k = 0; k < SPL; k++) {
                    pm[k] = ld_relaxed4(pml + k * 256); pl[k] = ld_relaxed2(pml + k * 256 + 4);
#pragma unroll
                    for (int i = 0; i < 4; i++) pv[k][i] = ld_relaxed4(po + k * 256 + (i >> 1) * (IPP * 8) + (i & 1) * 4);
                }
#pragma unroll
                for (int k = 0; k < SPL; k++)
                    mis |= mis4(pm[k], pt) | (pl[k].x ^ pt) | (pl[k].y ^ pt) | mis4(pv[k][0], pt) | mis4(pv[k][1], pt) | mis4(pv[k][2], pt) | mis4(pv[k][3], pt);
                if (!(mis & 1u)) break;
                SPIN_GUARD(it, 1u << 22);
            }
            __syncwarp();
            float m0[SPL], m1[SPL];
#pragma unroll
            for (int k = 0; k < SPL; k++) { m0[k] = __uint_as_float(hi16x2(pm[k].x, pm[k].y)); m1[k] = __uint_as_float(hi16x2(pm[k].z, pm[k].w)); }
            const float X0 = warp_max(fmaxf(m0[0], m0[SPL - 1])), X1 = warp_max(fmaxf(m1[0], m1[SPL - 1]));
            float v[16], den[2] = {0.f, 0.f};
#pragma unroll
            for (int i = 0; i < 16; i++) v[i] = 0.f;
#pragma unroll
            for (int k = 0; k < SPL; k++) {
                const float e0 = ex2(m0[k] - X0), e1 = ex2(m1[k] - X1);
#pragma unroll
                for (int i = 0; i < 4; i++) {
                    v[4 * i] += e0 * untag(pv[k][i].x); v[4 * i + 1] += e1 * untag(pv[k][i].y);
                    v[4 * i + 2] += e0 * untag(pv[k][i].z); v[4 * i + 3] += e1 * untag(pv[k][i].w);
                }
                den[0] += e0 * untag(pl[k].x); den[1] += e1 * untag(pl[k].y);
            }
            fold<1, 2>(den, lane);
            fold<8, 16>(v, lane); den[0] += __shfl_xor_sync(0xffffffffu, den[0], 16);
            fold<4, 8>(v, lane); den[0] += __shfl_xor_sync(0xffffffffu, den[0], 8);
            fold<2, 4>(v, lane); den[0] += __shfl_xor_sync(0xffffffffu, den[0], 4);
            fold<1, 2>(v, lane); den[0] += __shfl_xor_sync(0xffffffffu, den[0], 1);
            v[0] += __shfl_xor_sync(0xffffffffu, v[0], 1);
            if (!(lane & 1)) st_relaxed(dst, tag_bf16(__fdividef(v[0], den[0]), tag));
            if (lane == 0) red_xor(&g_omask[pair].v, 1u << u);
        }
        uint32_t it = 0;
        while (s_misc[1] < (uint32_t)NPAIR) {
            __nanosleep(500);
            SPIN_GUARD(it, 1u << 20);
        }
    }
    for (int task = (warp - 4) * gridDim.x + blockIdx.x; task < NFTASK; task += gridDim.x * 5) {
        const int blk = task >> 4, fl = (task & 15) * 2 + ((lane >> 2) & 1), mi = lane & 3;
        const int oidx = ((fl & 3) * 2 + (mi & 1)) * DM + blk * 16 + (fl >> 2) + (mi >> 1) * 8;
        const float xv = __bfloat162float(x[oidx]);
        const uint32_t* src = g_fin + (task * NFIN + lane) * 8;
        const bool has2 = lane == 16 || lane == 17;
        uint32_t it = 0;
        while (true) {
            const uint2 m = ld_relaxed2(&g_fmask[blk].v);
            const uint32_t lo = m.x ^ mflip, hi = (m.y ^ mflip) | ~3u;
            if ((lo & hi) == 0xffffffffu) break;
            if (__popc(lo) < 16) __nanosleep(300);
            SPIN_GUARD(it, 1u << 22);
        }
        uint4 p0, p1, e0, e1;
        e0 = e1 = make_uint4(0, 0, 0, 0);
        while (true) {
            p0 = ld_relaxed4(src); p1 = ld_relaxed4(src + 4);
            uint32_t mis = 0;
            if (has2) { e0 = ld_relaxed4(src + 128); e1 = ld_relaxed4(src + 132); mis = mis4(e0, tag) | mis4(e1, tag); }
            if (!((mis | mis4(p0, tag) | mis4(p1, tag)) & 1u)) break;
            SPIN_GUARD(it, 1u << 22);
        }
        __syncwarp();
        float v[8] = {untag(p0.x) + untag(e0.x), untag(p0.y) + untag(e0.y), untag(p0.z) + untag(e0.z), untag(p0.w) + untag(e0.w),
                      untag(p1.x) + untag(e1.x), untag(p1.y) + untag(e1.y), untag(p1.z) + untag(e1.z), untag(p1.w) + untag(e1.w)};
        fold<4, 4>(v, lane); fold<2, 2>(v, lane); fold<1, 1>(v, lane);
        const float sum = rbf(v[0] + __shfl_xor_sync(0xffffffffu, v[0], 8));
        const float gate = __shfl_down_sync(0xffffffffu, rbf(__fdividef(sum, 1.0f + __expf(-sum))), 16);
        if (lane < 8) out[oidx] = __float2bfloat16_rn(xv + rbf(sum * gate));
        if (task == 0 && lane == 0) g_epoch.v = epoch + 1;
    }
}

typedef CUresult (*EncodeTiledFn)(CUtensorMap*, CUtensorMapDataType, cuuint32_t, void*, const cuuint64_t*, const cuuint64_t*,
                                  const cuuint32_t*, const cuuint32_t*, CUtensorMapInterleave, CUtensorMapSwizzle,
                                  CUtensorMapL2promotion, CUtensorMapFloatOOBfill);

}

extern "C" void kernel_launch(void* const* d_in, const int* in_sizes, int n_in, void* d_out, int out_size) {
    (void)in_sizes; (void)n_in; (void)out_size;
    static EncodeTiledFn enc = nullptr;
    static int num_sms = 0;
    if (!enc) {
        cudaDriverEntryPointQueryResult qr;
        void* fn = nullptr;
        cudaGetDriverEntryPoint("cuTensorMapEncodeTiled", &fn, cudaEnableDefault, &qr);
        enc = (EncodeTiledFn)fn;
        cudaDeviceGetAttribute(&num_sms, cudaDevAttrMultiProcessorCount, 0);
        cudaFuncSetAttribute(fused_decode_kernel, cudaFuncAttributeMaxDynamicSharedMemorySize, SMEM_BYTES);
    }
    const __nv_bfloat16* x = (const __nv_bfloat16*)d_in[0];
    CUtensorMap mK, mV, mWq, mWg, mWu, mWd, mWo;
    const cuuint32_t es[3] = {1, 1, 1};
    auto kv_map = [&](CUtensorMap* m, void* p) {
        const cuuint64_t gd[3] = {64, (cuuint64_t)NPAIR * SK, 2};
        const cuuint64_t gs[2] = {256, 128};
        const cuuint32_t bx[3] = {64, TILE, 2};
        enc(m, CU_TENSOR_MAP_DATA_TYPE_BFLOAT16, 3, p, gd, gs, bx, es, CU_TENSOR_MAP_INTERLEAVE_NONE,
            CU_TENSOR_MAP_SWIZZLE_128B, CU_TENSOR_MAP_L2_PROMOTION_L2_256B, CU_TENSOR_MAP_FLOAT_OOB_FILL_NONE);
    };
    auto x_map = [&](CUtensorMap* m, void* p, int ncols) {
        const cuuint64_t gd[2] = {(cuuint64_t)ncols, DM};
        const cuuint64_t gs[1] = {(cuuint64_t)ncols * 2};
        const cuuint32_t bx[2] = {32, 192};
        enc(m, CU_TENSOR_MAP_DATA_TYPE_BFLOAT16, 2, p, gd, gs, bx, es, CU_TENSOR_MAP_INTERLEAVE_NONE,
            CU_TENSOR_MAP_SWIZZLE_64B, CU_TENSOR_MAP_L2_PROMOTION_L2_256B, CU_TENSOR_MAP_FLOAT_OOB_FILL_NONE);
    };
    auto y_map = [&](CUtensorMap* m, void* p, int nrows) {
        const cuuint64_t gd[2] = {DM, (cuuint64_t)nrows};
        const cuuint64_t gs[1] = {DM * 2};
        const cuuint32_t bx[2] = {64, 256};
        enc(m, CU_TENSOR_MAP_DATA_TYPE_BFLOAT16, 2, p, gd, gs, bx, es, CU_TENSOR_MAP_INTERLEAVE_NONE,
            CU_TENSOR_MAP_SWIZZLE_128B, CU_TENSOR_MAP_L2_PROMOTION_L2_128B, CU_TENSOR_MAP_FLOAT_OOB_FILL_NONE);
    };
    kv_map(&mK, d_in[1]);
    kv_map(&mV, d_in[2]);
    x_map(&mWq, d_in[3], NQC);
    y_map(&mWo, d_in[4], NQC);
    x_map(&mWg, d_in[6], FF);
    x_map(&mWu, d_in[7], FF);
    y_map(&mWd, d_in[8], FF);
    fused_decode_kernel<<<num_sms, NTHREADS, SMEM_BYTES>>>(mK, mV, mWq, mWg, mWu, mWd, mWo, x, (__nv_bfloat16*)d_out,
                                                                (const char*)d_in[3]);
}
```
